```python
import torch

def _softmax(x, axis=-1):
    return torch.softmax(x, dim=axis)
def _gelu(x):
    return torch.nn.functional.gelu(x, approximate="tanh")
def _silu(x):
    return torch.nn.functional.silu(x)
def _sigmoid(x):
    return torch.sigmoid(x)
def _layernorm(x, axis=-1, eps=1e-5):
    m = x.mean(dim=axis, keepdim=True)
    v = x.var(dim=axis, keepdim=True, unbiased=False)
    return (x - m) / torch.sqrt(v + eps)
def _scatter_add(tgt, idx, src, axis=0):
    return tgt.clone().index_add_(axis, idx, src)
def _segment_sum(src, seg, n):
    out = torch.zeros((n,) + src.shape[1:], dtype=src.dtype)
    return out.index_add_(0, seg, src)
def _pad(x, pw):
    flat = tuple(v for pair in reversed(pw) for v in pair)
    return torch.nn.functional.pad(x, flat)

kernel_name = 'standalone__mha_block_cached__near_ridge'

def setup_inputs():

    _w = (lambda a: (lambda t: t.to(torch.bfloat16) if t.is_floating_point() else t)(torch.as_tensor(a)))
    B, Sq, D = 8, 192, 448
    H, Sk, Dh = 16, 1024, 256
    return {
        "x": _w((lambda *s: torch.randn(*s, dtype=torch.bfloat16) * 0.8)(B, Sq, D)),
        "k_cache": _w((lambda *s: torch.randn(*s, dtype=torch.bfloat16) * 0.8)(B, H, Sk, Dh)),
        "v_cache": _w((lambda *s: torch.randn(*s, dtype=torch.bfloat16) * 0.05)(B, H, Sk, Dh)),
        "wq": _w((lambda *s: torch.randn(*s, dtype=torch.bfloat16) * 0.8)(D, H * Dh) * (D ** -0.5)),
        "wo": _w((lambda *s: torch.randn(*s, dtype=torch.bfloat16) * 0.05)(H * Dh, D) * ((H * Dh) ** -0.5)),
    }

def reference(x, k_cache, v_cache, wq, wo):
    B, Sq, D = x.shape
    H, Dh = 16, 256
    q = (lambda x, *d: x.permute(*d))((x @ wq).reshape(B, Sq, H, Dh), 0, 2, 1, 3)
    scores = torch.einsum("bhqd,bhkd->bhqk", q, k_cache) * (Dh ** -0.5)
    p = _softmax(scores, axis=-1)
    o = torch.einsum("bhqk,bhkd->bhqd", p, v_cache)
    return (lambda x, *d: x.permute(*d))(o, 0, 2, 1, 3).reshape(B, Sq, H * Dh) @ wo
```

```cpp
#include <cuda_runtime.h>
#include <cuda_bf16.h>
#include <cuda.h>
#include <stdint.h>
#include <type_traits>

namespace {

constexpr int NB = 8, SQ = 192, DM = 448, NH = 16, SK = 1024, DH = 256;
constexpr int SLOT = 32768;
constexpr int NS_O = 4;
constexpr int PST = 3;
constexpr int PMSG_W = 2176;
constexpr int NKT = SK / 64;
constexpr int NKC = DM / 64;
#define PF_HEAD 3

constexpr int OFF_MBOX = NS_O * SLOT;
constexpr int OFF_XBUF = 2 * 2 * SLOT;
constexpr int OFF_BAR = OFF_XBUF + 3 * SLOT;
static_assert(OFF_BAR >= OFF_MBOX + 12 * PST * PMSG_W, "smem layout");
constexpr int BAR_SF = 0;
constexpr int BAR_VF = 4;
constexpr int BAR_SREL = 8;
constexpr int BAR_VREL = 12;
constexpr int BAR_XFREE = 16;
constexpr int BAR_XF = 17;
constexpr int BAR_P = 20;
constexpr int NBARS = BAR_P + 12 * PST;
constexpr int SMEM_BYTES = OFF_BAR + NBARS * 8 + 1024;

constexpr int SLICES_PER_B = NKC * 3 * 4 * 4;

__device__ uint4 g_part[(size_t)NB * NH * NKC * 3 * 4 * 128];
__device__ unsigned int g_cnt[NB];
__device__ unsigned int g_done[NB];

#define TACC_BEGIN()
#define TACC_END(k)
#define TSTAMP(i)
#define TS_BEGIN()
#define TS_GT(j)
#define TS_END()
#define TS_EXTRA 0
__device__ __forceinline__ uint32_t smem_u32(const void* p) { return (uint32_t)__cvta_generic_to_shared(p); }

__device__ __forceinline__ void mbar_init(uint32_t bar, uint32_t cnt) {
  asm volatile("mbarrier.init.shared::cta.b64 [%0], %1;" ::"r"(bar), "r"(cnt) : "memory");
}
__device__ __forceinline__ void mbar_expect_tx(uint32_t bar, uint32_t bytes) {
  asm volatile("mbarrier.arrive.expect_tx.shared::cta.b64 _, [%0], %1;" ::"r"(bar), "r"(bytes) : "memory");
}
__device__ __forceinline__ void mbar_arrive_remote(uint32_t rbar) {
  asm volatile("mbarrier.arrive.shared::cluster.b64 _, [%0];" ::"r"(rbar) : "memory");
}
constexpr uint32_t SPIN_LIMIT = 1u << 22;
__device__ __forceinline__ void mbar_wait(uint32_t bar, uint32_t parity) {
  asm volatile(
      "{\n.reg .pred p, q;\n.reg .u32 n;\n"
      "mbarrier.try_wait.parity.shared::cta.b64 p, [%0], %1;\n"
      "@p bra.uni DONE_%=;\n"
      "mov.u32 n, 0;\n"
      "LOOP_%=:\n"
      "mbarrier.try_wait.parity.shared::cta.b64 p, [%0], %1;\n"
      "@p bra.uni DONE_%=;\n"
      "add.u32 n, n, 1;\n"
      "setp.lt.u32 q, n, 4194304;\n"
      "@q bra.uni LOOP_%=;\n"
      "trap;\n"
      "DONE_%=:\n}"
      ::"r"(bar), "r"(parity) : "memory");
}
__device__ __forceinline__ uint32_t mapa(uint32_t addr, uint32_t rank) {
  uint32_t r;
  asm volatile("mapa.shared::cluster.u32 %0, %1, %2;" : "=r"(r) : "r"(addr), "r"(rank));
  return r;
}
__device__ __forceinline__ void cluster_sync_all() {
  asm volatile("barrier.cluster.arrive.release.aligned;\nbarrier.cluster.wait.acquire.aligned;" ::: "memory");
}
__device__ __forceinline__ void tma_2d(uint32_t dst, const CUtensorMap* tm, int c0, int c1, uint32_t bar) {
  asm volatile("cp.async.bulk.tensor.2d.shared::cluster.global.mbarrier::complete_tx::bytes [%0], [%1, {%3, %4}], [%2];"
               ::"r"(dst), "l"(tm), "r"(bar), "r"(c0), "r"(c1) : "memory");
}
__device__ __forceinline__ void tma_3d(uint32_t dst, const CUtensorMap* tm, int c0, int c1, int c2, uint32_t bar) {
  asm volatile("cp.async.bulk.tensor.3d.shared::cluster.global.mbarrier::complete_tx::bytes [%0], [%1, {%3, %4, %5}], [%2];"
               ::"r"(dst), "l"(tm), "r"(bar), "r"(c0), "r"(c1), "r"(c2) : "memory");
}
__device__ __forceinline__ void tma_3d_ef(uint32_t dst, const CUtensorMap* tm, int c0, int c1, int c2, uint32_t bar) {
  asm volatile("{\n.reg .b64 pol;\ncreatepolicy.fractional.L2::evict_first.b64 pol, 1.0;\n"
               "cp.async.bulk.tensor.3d.shared::cluster.global.mbarrier::complete_tx::bytes.L2::cache_hint [%0], [%1, {%3, %4, %5}], [%2], pol;\n}"
               ::"r"(dst), "l"(tm), "r"(bar), "r"(c0), "r"(c1), "r"(c2) : "memory");
}
__device__ __forceinline__ void l2_prefetch(const void* p, uint32_t bytes) {
  asm volatile("cp.async.bulk.prefetch.L2.global [%0], %1;" ::"l"(p), "r"(bytes) : "memory");
}
__device__ __forceinline__ void st_async_v4(uint32_t raddr, uint32_t a, uint32_t b, uint32_t c, uint32_t d, uint32_t rbar) {
  asm volatile("st.async.weak.shared::cluster.mbarrier::complete_tx::bytes.v4.b32 [%0], {%1, %2, %3, %4}, [%5];"
               ::"r"(raddr), "r"(a), "r"(b), "r"(c), "r"(d), "r"(rbar) : "memory");
}
__device__ __forceinline__ void lds_v4(uint32_t addr, uint32_t& a, uint32_t& b, uint32_t& c, uint32_t& d) {
  asm volatile("ld.shared.v4.b32 {%0, %1, %2, %3}, [%4];" : "=r"(a), "=r"(b), "=r"(c), "=r"(d) : "r"(addr) : "memory");
}
__device__ __forceinline__ uint32_t pack_bf16(float lo, float hi) {
  uint32_t r;
  asm("cvt.rn.bf16x2.f32 %0, %1, %2;" : "=r"(r) : "f"(hi), "f"(lo));
  return r;
}
__device__ __forceinline__ uint32_t pack_bf16_v(float lo, float hi) {
  uint32_t r;
  asm volatile("cvt.rn.bf16x2.f32 %0, %1, %2;" : "=r"(r) : "f"(hi), "f"(lo));
  return r;
}
__device__ __forceinline__ float ex2v(float x) {
  float r;
  asm volatile("ex2.approx.ftz.f32 %0, %1;" : "=f"(r) : "f"(x));
  return r;
}
__device__ __forceinline__ float ex2(float x) {
  float r;
  asm("ex2.approx.ftz.f32 %0, %1;" : "=f"(r) : "f"(x));
  return r;
}

__device__ __forceinline__ uint64_t make_desc(uint32_t addr, uint32_t lbo, uint32_t sbo) {
  return (uint64_t)((addr & 0x3FFFF) >> 4) | ((uint64_t)(lbo >> 4) << 16) | ((uint64_t)(sbo >> 4) << 32) | (1ull << 62);
}
__device__ __forceinline__ void wg_fence() { asm volatile("wgmma.fence.sync.aligned;" ::: "memory"); }
__device__ __forceinline__ void wg_commit() { asm volatile("wgmma.commit_group.sync.aligned;" ::: "memory"); }
template <int N> __device__ __forceinline__ void wg_wait() { asm volatile("wgmma.wait_group.sync.aligned %0;" ::"n"(N) : "memory"); }
template <int N> __device__ __forceinline__ void fence_regs(float (&r)[N]) {
#pragma unroll
  for (int i = 0; i < N; i++) asm volatile("" : "+f"(r[i])::"memory");
}

#define F8(a, o) "+f"(a[o + 0]), "+f"(a[o + 1]), "+f"(a[o + 2]), "+f"(a[o + 3]), "+f"(a[o + 4]), "+f"(a[o + 5]), "+f"(a[o + 6]), "+f"(a[o + 7])
#define F32(a, o) F8(a, o), F8(a, o + 8), F8(a, o + 16), F8(a, o + 24)
#define F128(a) F32(a, 0), F32(a, 32), F32(a, 64), F32(a, 96)
#define D32 "{%0, %1, %2, %3, %4, %5, %6, %7, %8, %9, %10, %11, %12, %13, %14, %15, %16, %17, %18, %19, %20, %21, %22, %23, %24, %25, %26, %27, %28, %29, %30, %31}"
#define D64 "{%0, %1, %2, %3, %4, %5, %6, %7, %8, %9, %10, %11, %12, %13, %14, %15, %16, %17, %18, %19, %20, %21, %22, %23, %24, %25, %26, %27, %28, %29, %30, %31, " \
  "%32, %33, %34, %35, %36, %37, %38, %39, %40, %41, %42, %43, %44, %45, %46, %47, %48, %49, %50, %51, %52, %53, %54, %55, %56, %57, %58, %59, %60, %61, %62, %63}"
#define D128 "{%0, %1, %2, %3, %4, %5, %6, %7, %8, %9, %10, %11, %12, %13, %14, %15, %16, %17, %18, %19, %20, %21, %22, %23, %24, %25, %26, %27, %28, %29, %30, %31, " \
  "%32, %33, %34, %35, %36, %37, %38, %39, %40, %41, %42, %43, %44, %45, %46, %47, %48, %49, %50, %51, %52, %53, %54, %55, %56, %57, %58, %59, %60, %61, %62, %63, " \
  "%64, %65, %66, %67, %68, %69, %70, %71, %72, %73, %74, %75, %76, %77, %78, %79, %80, %81, %82, %83, %84, %85, %86, %87, %88, %89, %90, %91, %92, %93, %94, %95, " \
  "%96, %97, %98, %99, %100, %101, %102, %103, %104, %105, %106, %107, %108, %109, %110, %111, %112, %113, %114, %115, %116, %117, %118, %119, %120, %121, %122, %123, %124, %125, %126, %127}"

template <int O>
__device__ __forceinline__ void wgmma_n128_ss(float (&d)[128], uint64_t da, uint64_t db, int scale_d) {
  asm volatile("{\n.reg .pred p;\nsetp.ne.b32 p, %66, 0;\n"
               "wgmma.mma_async.sync.aligned.m64n128k16.f32.bf16.bf16 " D64 ", %64, %65, p, 1, 1, 0, 1;\n}"
               : F32(d, O), F32(d, O + 32) : "l"(da), "l"(db), "r"(scale_d));
}
template <int O>
__device__ __forceinline__ void wgmma_n128_rs(float (&d)[128], uint32_t a0, uint32_t a1, uint32_t a2, uint32_t a3, uint64_t db, int scale_d) {
  asm volatile("{\n.reg .pred p;\nsetp.ne.b32 p, %69, 0;\n"
               "wgmma.mma_async.sync.aligned.m64n128k16.f32.bf16.bf16 " D64 ", {%64, %65, %66, %67}, %68, p, 1, 1, 1;\n}"
               : F32(d, O), F32(d, O + 32) : "r"(a0), "r"(a1), "r"(a2), "r"(a3), "l"(db), "r"(scale_d));
}
__device__ __forceinline__ void wgmma_n256_ss(float (&d)[128], uint64_t da, uint64_t db, int scale_d) {
  asm volatile("{\n.reg .pred p;\nsetp.ne.b32 p, %130, 0;\n"
               "wgmma.mma_async.sync.aligned.m64n256k16.f32.bf16.bf16 " D128 ", %128, %129, p, 1, 1, 0, 1;\n}"
               : F128(d) : "l"(da), "l"(db), "r"(scale_d));
}
__device__ __forceinline__ void wgmma_n256_rs(float (&d)[128], uint32_t a0, uint32_t a1, uint32_t a2, uint32_t a3, uint64_t db, int scale_d) {
  asm volatile("{\n.reg .pred p;\nsetp.ne.b32 p, %133, 0;\n"
               "wgmma.mma_async.sync.aligned.m64n256k16.f32.bf16.bf16 " D128 ", {%128, %129, %130, %131}, %132, p, 1, 1, 1;\n}"
               : F128(d) : "r"(a0), "r"(a1), "r"(a2), "r"(a3), "l"(db), "r"(scale_d));
}
template <int TB>
__device__ __forceinline__ void wgmma_n64_rs(float (&d)[32], uint32_t a0, uint32_t a1, uint32_t a2, uint32_t a3, uint64_t db, int scale_d) {
  asm volatile("{\n.reg .pred p;\nsetp.ne.b32 p, %37, 0;\n"
               "wgmma.mma_async.sync.aligned.m64n64k16.f32.bf16.bf16 " D32 ", {%32, %33, %34, %35}, %36, p, 1, 1, %38;\n}"
               : F32(d, 0) : "r"(a0), "r"(a1), "r"(a2), "r"(a3), "l"(db), "r"(scale_d), "n"(TB));
}

__device__ __forceinline__ void token_wait(int wg) { asm volatile("bar.sync %0, 256;" ::"r"(wg + 1) : "memory"); }
__device__ __forceinline__ void token_pass(int wg) { asm volatile("bar.arrive %0, 256;" ::"r"(wg == 2 ? 1 : wg + 2) : "memory"); }

__device__ __forceinline__ void slice_load(int s, int lane, uint4 (&v)[NH]) {
  const int b = s / SLICES_PER_B, r = s % SLICES_PER_B;
  const uint4* src = g_part + ((size_t)b * NH * NKC * 3 * 4 * 128 + (size_t)r * 32 + lane);
  constexpr size_t HSTRIDE = (size_t)NKC * 3 * 4 * 128;
#pragma unroll
  for (int i = 0; i < NH; i++) v[i] = __ldcg(src + (size_t)i * HSTRIDE);
}
__device__ __forceinline__ void slice_store(int s, int lane, const uint4 (&v)[NH], __nv_bfloat16* out) {
  const int b = s / SLICES_PER_B, r = s % SLICES_PER_B;
  const int warp = r & 3, j = (r >> 2) & 3, cw = r >> 4;
  const int w = cw % 3, c = cw / 3;
  float acc[8];
#pragma unroll
  for (int i = 0; i < 8; i++) acc[i] = 0.f;
#pragma unroll
  for (int i = 0; i < NH; i++) {
    acc[0] += __uint_as_float(v[i].x << 16); acc[1] += __uint_as_float(v[i].x & 0xffff0000u);
    acc[2] += __uint_as_float(v[i].y << 16); acc[3] += __uint_as_float(v[i].y & 0xffff0000u);
    acc[4] += __uint_as_float(v[i].z << 16); acc[5] += __uint_as_float(v[i].z & 0xffff0000u);
    acc[6] += __uint_as_float(v[i].w << 16); acc[7] += __uint_as_float(v[i].w & 0xffff0000u);
  }
  const int g = lane >> 2, q = lane & 3;
  const int row = w * 64 + warp * 16 + g;
  const int col = c * 64 + j * 16 + 2 * q;
  uint32_t* o = reinterpret_cast<uint32_t*>(out + ((size_t)(b * SQ + row) * DM + col));
  o[0] = pack_bf16(acc[0], acc[1]);
  o[8 * DM / 2] = pack_bf16(acc[2], acc[3]);
  o[4] = pack_bf16(acc[4], acc[5]);
  o[8 * DM / 2 + 4] = pack_bf16(acc[6], acc[7]);
}

__device__ __forceinline__ void wait_all(int tid, int idx) {
  if (tid == 0) {
    uint32_t n = 0;
    while (true) {
      unsigned int v;
      asm volatile("ld.acquire.gpu.global.u32 %0, [%1];" : "=r"(v) : "l"(g_cnt + idx) : "memory");
      if (v >= 64u * 12u) break;
      __nanosleep(64);
      if (++n > SPIN_LIMIT) __trap();
    }
  }
  asm volatile("bar.sync 4, 384;" ::: "memory");
}

struct Maps {
  const CUtensorMap *x, *wq, *k, *v, *wo;
  const char *kptr, *vptr, *xptr, *woptr;
};
__device__ __forceinline__ void load_chunk(const Maps& m, int c, uint32_t sbase, int b, int h) {
  const uint32_t stage = c % 3;
  const uint32_t dst = sbase + stage * (2 * SLOT);
  const uint32_t bar = sbase + OFF_BAR + (BAR_SF + stage) * 8;
  mbar_expect_tx(bar, SLOT + SQ * 128);
  tma_2d(dst, m.x, c * 64, b * SQ, bar);
  tma_3d(dst + SLOT, m.wq, 0, c * 64, h * 4, bar);
}
__device__ __forceinline__ void issue_ring(const Maps& m, int n, uint32_t sbase, int b0, int h, uint32_t rank) {
  if (n >= 2 * NKT + NKC) return;
  const uint32_t slot = (n + 2) & 3;
  const uint32_t dst = sbase + slot * SLOT;
  const uint32_t bar = sbase + OFF_BAR + (BAR_VF + slot) * 8;
  mbar_expect_tx(bar, SLOT);
  if (n < 2 * NKT) tma_3d_ef(dst, rank ? m.v : m.k, 0, ((b0 + 4 * (n >> 4)) * NH + h) * SK + (n & 15) * 64, 0, bar);
  else tma_2d(dst, m.wo, (n - 2 * NKT) * 64, h * DH, bar);
}
__device__ __forceinline__ void store_chunk(uint4* dst, const float (&a)[32]) {
#pragma unroll
  for (int j = 0; j < 4; j++) {
    uint4 w;
    w.x = pack_bf16(a[8 * j], a[8 * j + 1]);
    w.y = pack_bf16(a[8 * j + 2], a[8 * j + 3]);
    w.z = pack_bf16(a[8 * j + 4], a[8 * j + 5]);
    w.w = pack_bf16(a[8 * j + 6], a[8 * j + 7]);
    dst[j * 128] = w;
  }
}
__device__ __forceinline__ void pf_tile(const Maps& m, int b0, int h, int it, int kv, int j) {
  if (j < NKT) l2_prefetch((kv ? m.vptr : m.kptr) + ((size_t)((b0 + 4 * it) * NH + h) * NKT + j) * SLOT, SLOT);
}

__device__ __forceinline__ uint32_t release_slot(uint32_t cnt_addr, int lane) {
  uint32_t old = 0;
  if (lane == 0) asm volatile("atom.relaxed.cta.shared.inc.u32 %0, [%1], 11;" : "=r"(old) : "r"(cnt_addr) : "memory");
  return old;
}

__global__ void __cluster_dims__(2, 1, 1) __launch_bounds__(384, 1)
mha_kernel(const __grid_constant__ CUtensorMap tm_x, const __grid_constant__ CUtensorMap tm_wq,
           const __grid_constant__ CUtensorMap tm_k, const __grid_constant__ CUtensorMap tm_v,
           const __grid_constant__ CUtensorMap tm_wo, const __nv_bfloat16* __restrict__ kptr,
           const __nv_bfloat16* __restrict__ vptr, const __nv_bfloat16* __restrict__ xptr,
           const __nv_bfloat16* __restrict__ woptr, __nv_bfloat16* __restrict__ out) {
  extern __shared__ uint8_t smem_raw[];
  const uint32_t sbase = (smem_u32(smem_raw) + 1023u) & ~1023u;
  const uint32_t bars = sbase + OFF_BAR;
  const int tid = threadIdx.x;
  const int warp = __shfl_sync(0xffffffffu, tid >> 5, 0), lane = tid & 31;
  const int wg = warp >> 2;
  TS_GT(2);
  uint32_t rank;
  asm volatile("mov.u32 %0, %%cluster_ctarank;" : "=r"(rank));
  const int cl = blockIdx.x >> 1;
  const int h = cl & 15;
  const int b0 = cl >> 4;

  Maps m{&tm_x, &tm_wq, &tm_k, &tm_v, &tm_wo, reinterpret_cast<const char*>(kptr), reinterpret_cast<const char*>(vptr),
         reinterpret_cast<const char*>(xptr), reinterpret_cast<const char*>(woptr)};
  if (tid == 0) {
    for (int i = 0; i < 8; i++) {
      mbar_init(bars + i * 8, 1);
      asm volatile("st.shared.u32 [%0], 0;" ::"r"(bars + (BAR_SREL + i) * 8) : "memory");
    }
    asm volatile("fence.mbarrier_init.release.cluster;" ::: "memory");
    asm volatile("fence.proxy.async.shared::cta;" ::: "memory");
    for (int i = 0; i < 3; i++) load_chunk(m, i, sbase, b0 + 4 * rank, h);
  } else if (tid == 32) {
    mbar_init(bars + BAR_XFREE * 8, 1);
    mbar_init(bars + BAR_XF * 8, 1);
    for (int i = 0; i < 12 * PST; i++) mbar_init(bars + (BAR_P + i) * 8, 1);
    if (rank == 1) {
      for (int i = 0; i < 12 * PST; i++) mbar_expect_tx(bars + (BAR_P + i) * 8, PMSG_W);
    } else {
      mbar_expect_tx(bars + BAR_XF * 8, 3 * SLOT);
    }
    asm volatile("fence.mbarrier_init.release.cluster;" ::: "memory");
  }
  TS_BEGIN();
  __syncthreads();
  asm volatile("barrier.cluster.arrive.relaxed.aligned;\nbarrier.cluster.wait.aligned;" ::: "memory");
  TS_GT(0);
  TSTAMP(0);

  uint32_t sph = 0;
  uint32_t q[64];
  {
    float acc[128];
#pragma unroll
    for (int i = 0; i < 128; i++) acc[i] = 0.f;
    auto after_chunk = [&](int c) {
      if (c < 4) load_chunk(m, c + 3, sbase, b0 + 4 * rank, h);
      else if (c == 5) {
        if (rank == 0) mbar_arrive_remote(mapa(bars + BAR_XFREE * 8, 1));
      } else {
        issue_ring(m, c - 4, sbase, b0, h, rank);
        issue_ring(m, c - 3, sbase, b0, h, rank);
      }
    };
    uint32_t st = 0, prev = 0;
#pragma unroll 1
    for (int kc = 0; kc < NKC; kc++) {
      mbar_wait(bars + (BAR_SF + st) * 8, (sph >> st) & 1);
      sph ^= 1u << st;
      const uint64_t da = make_desc(sbase + st * (2 * SLOT) + wg * 8192, 16, 1024);
      const uint64_t db = make_desc(sbase + st * (2 * SLOT) + SLOT, 8192, 1024);
      wg_fence();
#pragma unroll
      for (int ks = 0; ks < 4; ks++) wgmma_n256_ss(acc, da + ks * 2, db + ks * 128, (kc | ks) != 0);
      wg_commit();
      if (rank == 0 && (tid & 127) == 64 && wg < 2 && kc < PF_HEAD) pf_tile(m, b0, h, 0, wg, kc);
      if (kc > 0) {
        wg_wait<1>();
        if (release_slot(bars + (BAR_SREL + prev) * 8, lane) == 11) after_chunk(kc - 1);
      }
      prev = st;
      st = st == 2 ? 0 : st + 1;
      TSTAMP(42 + kc);
    }
    wg_wait<0>();
    fence_regs(acc);
    if (release_slot(bars + (BAR_SREL + prev) * 8, lane) == 11) after_chunk(NKC - 1);
#pragma unroll
    for (int i = 63; i >= 0; i--) q[i] = pack_bf16_v(acc[2 * i], acc[2 * i + 1]);
  }
  TSTAMP(1);

  int seq = 0;
  auto oproj = [&](uint32_t (&of)[64]) {
    uint32_t tid2;
    asm volatile("mov.u32 %0, %%tid.x;" : "=r"(tid2));
    uint4* dst = g_part + ((size_t)((b0 + 4 * rank) * NH + h) * NKC * 3 * 4 * 128 + (size_t)wg * 4 * 128 + (tid2 & 127));
    float acc[2][32];
#pragma unroll
    for (int i = 0; i < 32; i++) { acc[0][i] = 0.f; acc[1][i] = 0.f; }
#pragma unroll
    for (int c = 0; c <= NKC; c++) {
      constexpr int n0 = 2 * NKT;
      if (c < NKC) {
        const uint32_t slot = (n0 + c + 2) & 3;
        { TACC_BEGIN(); mbar_wait(bars + (BAR_VF + slot) * 8, ((n0 + c) >> 2) & 1); if (lane == 0) TACC_END(2); }
        uint32_t sb2;
        asm volatile("mov.u32 %0, %1;" : "=r"(sb2) : "r"(sbase));
        const uint64_t db = make_desc(sb2 + slot * SLOT, 8192, 1024);
        wg_fence();
#pragma unroll
        for (int ks = 0; ks < 16; ks++)
          wgmma_n64_rs<1>(acc[c & 1], of[4 * ks], of[4 * ks + 1], of[4 * ks + 2], of[4 * ks + 3], db + ks * 128, ks != 0);
        wg_commit();
      }
      if (c > 0) {
        if (c < NKC) wg_wait<1>(); else wg_wait<0>();
        float(&a)[32] = acc[(c - 1) & 1];
        fence_regs(a);
        uint32_t rel = 0;
        if (c - 1 + NS_O < NKC) rel = release_slot(bars + (BAR_VREL + ((n0 + c + 1) & 3)) * 8, lane);
        store_chunk(dst + (size_t)(c - 1) * (3 * 4 * 128), a);
        if (rel == 11) issue_ring(m, n0 + c - 1 + NS_O, sbase, b0, h, rank);
      }
      TSTAMP(50 + c);
    }
  };
  if (rank == 0) {
    uint32_t pstage = 0, pphase = 0;
    const uint32_t mbox_r = mapa(sbase + OFF_MBOX + warp * (PST * PMSG_W) + lane * 16, 1);
    const uint32_t pfull_r = mapa(bars + (BAR_P + warp * PST) * 8, 1);
    const uint32_t pempty = bars + (BAR_P + warp * PST) * 8;
    const uint32_t xbuf = sbase + OFF_XBUF + warp * 8192 + lane * 16;
    const float cs = 0.0625f * 1.4426950408889634f;
#pragma unroll 1
    for (int it = 0; it < 2; it++) {
      if (it == 1) {
        mbar_wait(bars + BAR_XF * 8, 0);
#pragma unroll
        for (int j = 0; j < 16; j++) lds_v4(xbuf + j * 512, q[4 * j], q[4 * j + 1], q[4 * j + 2], q[4 * j + 3]);
      }
      float n0 = INFINITY, n1 = INFINITY, l0 = 0.f, l1 = 0.f;
      float sA[32], sB[32];
#pragma unroll
      for (int i = 0; i < 32; i++) { sA[i] = 0.f; sB[i] = 0.f; }
      float a0 = 1.f, a1 = 1.f;
      auto new_ref = [&](float (&s)[32]) {
        float mx0 = fmaxf(s[0], s[1]), mx1 = fmaxf(s[2], s[3]);
#pragma unroll
        for (int j = 1; j < 8; j++) {
          mx0 = fmaxf(mx0, fmaxf(s[4 * j], s[4 * j + 1]));
          mx1 = fmaxf(mx1, fmaxf(s[4 * j + 2], s[4 * j + 3]));
        }
        mx0 = fmaxf(mx0, __shfl_xor_sync(0xffffffffu, mx0, 1));
        mx1 = fmaxf(mx1, __shfl_xor_sync(0xffffffffu, mx1, 1));
        mx0 = fmaxf(mx0, __shfl_xor_sync(0xffffffffu, mx0, 2));
        mx1 = fmaxf(mx1, __shfl_xor_sync(0xffffffffu, mx1, 2));
        const float n0n = fminf(n0, -mx0 * cs), n1n = fminf(n1, -mx1 * cs);
        a0 = ex2(n0n - n0); a1 = ex2(n1n - n1);
        n0 = n0n; n1 = n1n;
        l0 *= a0; l1 *= a1;
      };
      auto step = [&](float (&s)[32], float (&sn)[32], uint64_t db, auto mma_tag, bool fresh_ref, bool last) {
        constexpr bool MMA = decltype(mma_tag)::value;
        { TACC_BEGIN(); mbar_wait(pempty + pstage * 8, pphase); if (lane == 0) TACC_END(6 + it); }
        uint32_t dst = mbox_r + pstage * PMSG_W;
        uint32_t rb = pfull_r + pstage * 8;
        float s0 = 0.f, s1 = 0.f;
        uint32_t p[4];
        if (MMA) wg_fence();
#pragma unroll
        for (int ks = 0; ks < 16; ks++) {
          if (MMA)
            wgmma_n64_rs<0>(sn, q[4 * ks], q[4 * ks + 1], q[4 * ks + 2], q[4 * ks + 3], db + (ks >> 2) * 512 + (ks & 3) * 2, ks != 0);
          const float nn = (ks & 1) ? n1 : n0;
          const float e0 = ex2v(fmaf(s[2 * ks], cs, nn)), e1 = ex2v(fmaf(s[2 * ks + 1], cs, nn));
          if (ks & 1) s1 += e0 + e1; else s0 += e0 + e1;
          p[ks & 3] = pack_bf16(e0, e1);
          if ((ks & 3) == 3) st_async_v4(dst + (ks >> 2) * 512, p[0], p[1], p[2], p[3], rb);
        }
        if (MMA) wg_commit();
        if (!fresh_ref && __any_sync(0xffffffffu, !(s0 <= 1048576.f) || !(s1 <= 1048576.f))) {
          if ((lane & 3) == 0) st_async_v4(dst + 2048 - lane * 12, 0xbf800000u, 0u, 0u, 0u, rb);
          if (++pstage == PST) { pstage = 0; pphase ^= 1; }
          new_ref(s);
          mbar_wait(pempty + pstage * 8, pphase);
          dst = mbox_r + pstage * PMSG_W;
          rb = pfull_r + pstage * 8;
          s0 = 0.f; s1 = 0.f;
#pragma unroll
          for (int ks = 0; ks < 16; ks++) {
            const float nn = (ks & 1) ? n1 : n0;
            const float e0 = ex2(fmaf(s[2 * ks], cs, nn)), e1 = ex2(fmaf(s[2 * ks + 1], cs, nn));
            if (ks & 1) s1 += e0 + e1; else s0 += e0 + e1;
            p[ks & 3] = pack_bf16(e0, e1);
            if ((ks & 3) == 3) st_async_v4(dst + (ks >> 2) * 512, p[0], p[1], p[2], p[3], rb);
          }
        }
        l0 += s0; l1 += s1;
        float i0 = 0.f, i1 = 0.f;
        if (last) {
          float t0 = l0 + __shfl_xor_sync(0xffffffffu, l0, 1);
          float t1 = l1 + __shfl_xor_sync(0xffffffffu, l1, 1);
          t0 += __shfl_xor_sync(0xffffffffu, t0, 2);
          t1 += __shfl_xor_sync(0xffffffffu, t1, 2);
          i0 = __frcp_rn(t0); i1 = __frcp_rn(t1);
        }
        if ((lane & 3) == 0)
          st_async_v4(dst + 2048 - lane * 12, __float_as_uint(a0), __float_as_uint(a1), __float_as_uint(i0), __float_as_uint(i1), rb);
        a0 = 1.f; a1 = 1.f;
        if (++pstage == PST) { pstage = 0; pphase ^= 1; }
      };
      auto kdesc = [&]() {
        const uint32_t slot = (seq + 2) & 3;
        { TACC_BEGIN(); mbar_wait(bars + (BAR_VF + slot) * 8, (seq >> 2) & 1); if (lane == 0) TACC_END(4 + it); }
        return make_desc(sbase + slot * SLOT, 16, 1024);
      };
      auto kdone = [&]() {
        if (release_slot(bars + (BAR_VREL + ((seq + 2) & 3)) * 8, lane) == 11) { TACC_BEGIN(); issue_ring(m, seq + NS_O, sbase, b0, h, 0); TACC_END(it); }
        __syncwarp();
        seq++;
      };
      {
        const uint64_t db = kdesc();
        wg_fence();
#pragma unroll
        for (int ks = 0; ks < 16; ks++)
          wgmma_n64_rs<0>(sA, q[4 * ks], q[4 * ks + 1], q[4 * ks + 2], q[4 * ks + 3], db + (ks >> 2) * 512 + (ks & 3) * 2, ks != 0);
        wg_commit();
        if (it == 1 && release_slot(bars + (BAR_SREL + 2) * 8, lane) == 11) {
          mbar_expect_tx(bars + BAR_XF * 8, 3 * SLOT);
          mbar_arrive_remote(mapa(bars + BAR_XFREE * 8, 1));
        }
        wg_wait<0>();
        fence_regs(sA);
        kdone();
        new_ref(sA);
      }
#pragma unroll 1
      for (int t = 0; t < NKT; t += 2) {
        step(sA, sB, kdesc(), std::true_type{}, t == 0, false);
        wg_wait<0>();
        fence_regs(sB);
        kdone();
        TSTAMP(2 + it * 20 + t);
        if (it == 1 && tid == 32 && t >= 2)
          l2_prefetch(m.woptr + (size_t)h * DH * DM * 2 + (size_t)((t >> 1) - 1) * SLOT, SLOT);
        if (t + 2 < NKT) {
          step(sB, sA, kdesc(), std::true_type{}, false, false);
          wg_wait<0>();
          fence_regs(sA);
          kdone();
        } else {
          step(sB, sA, 0, std::false_type{}, false, true);
        }
        TSTAMP(3 + it * 20 + t);
      }
    }
    uint32_t of[64];
    mbar_wait(bars + BAR_XF * 8, 1);
#pragma unroll
    for (int j = 0; j < 16; j++) lds_v4(xbuf + j * 512, of[4 * j], of[4 * j + 1], of[4 * j + 2], of[4 * j + 3]);
    oproj(of);
  } else {
    uint32_t pstage = 0, pphase = 0;
    const uint32_t mbox = sbase + OFF_MBOX + warp * (PST * PMSG_W) + lane * 16;
    const uint32_t mstat = sbase + OFF_MBOX + warp * (PST * PMSG_W) + 2048 + (lane >> 2) * 16;
    const uint32_t pfull = bars + (BAR_P + warp * PST) * 8;
    const uint32_t pempty_r = mapa(bars + (BAR_P + warp * PST) * 8, 0);
    const uint32_t xbuf_r = mapa(sbase + OFF_XBUF + warp * 8192 + lane * 16, 0);
    const uint32_t xf_r = mapa(bars + BAR_XF * 8, 0);
    {
      asm volatile("bar.sync 4, 384;" ::: "memory");
      if (lane < PST) mbar_arrive_remote(pempty_r + lane * 8);
      __syncwarp();
      mbar_wait(bars + BAR_XFREE * 8, 0);
#pragma unroll
      for (int j = 0; j < 16; j++) st_async_v4(xbuf_r + j * 512, q[4 * j], q[4 * j + 1], q[4 * j + 2], q[4 * j + 3], xf_r);
      if (wg == 2) token_pass(2);
    }
#pragma unroll 1
    for (int it = 0; it < 2; it++) {
      uint32_t of[64];
      {
        float o[128];
#pragma unroll
        for (int i = 0; i < 128; i++) o[i] = 0.f;
        uint32_t ua0 = 0x3f800000u, ua1 = 0x3f800000u;
        mbar_wait(pfull + pstage * 8, pphase);
        mbar_wait(bars + (BAR_VF + ((seq + 2) & 3)) * 8, (seq >> 2) & 1);
        uint32_t rel = 0;
        auto pv_step = [&](int t, bool last) {
          if (__any_sync(0xffffffffu, (ua0 != 0x3f800000u) || (ua1 != 0x3f800000u))) {
            if (ua0 == 0xbf800000u) {
              __syncwarp();
              if (lane == 0) {
                mbar_expect_tx(pfull + pstage * 8, PMSG_W);
                mbar_arrive_remote(pempty_r + pstage * 8);
              }
              if (++pstage == PST) { pstage = 0; pphase ^= 1; }
              mbar_wait(pfull + pstage * 8, pphase);
              asm volatile("ld.shared.v2.b32 {%0, %1}, [%2];" : "=r"(ua0), "=r"(ua1) : "r"(mstat + pstage * PMSG_W) : "memory");
            }
            const float a0 = __uint_as_float(ua0), a1 = __uint_as_float(ua1);
#pragma unroll
            for (int j = 0; j < 32; j++) {
              o[4 * j] *= a0; o[4 * j + 1] *= a0; o[4 * j + 2] *= a1; o[4 * j + 3] *= a1;
            }
          }
          uint32_t p[16];
          const uint32_t src = mbox + pstage * PMSG_W;
#pragma unroll
          for (int j = 0; j < 3; j++) lds_v4(src + j * 512, p[4 * j], p[4 * j + 1], p[4 * j + 2], p[4 * j + 3]);
          const uint64_t db = make_desc(sbase + ((seq + 2) & 3) * SLOT, 8192, 1024);
          { TACC_BEGIN(); token_wait(wg); if (lane == 0) TACC_END(8 + it); }
          wg_fence();
          wgmma_n256_rs(o, p[0], p[1], p[2], p[3], db, t != 0);
          wg_commit();
          wgmma_n256_rs(o, p[4], p[5], p[6], p[7], db + 128, 1);
          wgmma_n256_rs(o, p[8], p[9], p[10], p[11], db + 256, 1);
          wg_commit();
          wg_wait<1>();
          lds_v4(src + 3 * 512, p[12], p[13], p[14], p[15]);
          wg_fence();
          wgmma_n256_rs(o, p[12], p[13], p[14], p[15], db + 384, 1);
          wg_commit();
          token_pass(wg);
          if (!last) {
            if (lane == 0) {
              mbar_expect_tx(pfull + pstage * 8, PMSG_W);
              mbar_arrive_remote(pempty_r + pstage * 8);
            }
            if (++pstage == PST) { pstage = 0; pphase ^= 1; }
          }
          if (rel == 11) { TACC_BEGIN(); issue_ring(m, seq - 1 + NS_O, sbase, b0, h, 1); TACC_END(it); }
          seq++;
          if (!last) {
            { TACC_BEGIN(); mbar_wait(pfull + pstage * 8, pphase); if (lane == 0) TACC_END(6 + it); }
            asm volatile("ld.shared.v2.b32 {%0, %1}, [%2];" : "=r"(ua0), "=r"(ua1) : "r"(mstat + pstage * PMSG_W) : "memory");
            { TACC_BEGIN(); mbar_wait(bars + (BAR_VF + ((seq + 2) & 3)) * 8, (seq >> 2) & 1); if (lane == 0) TACC_END(4 + it); }
          }
          wg_wait<0>();
          fence_regs(o);
          rel = release_slot(bars + (BAR_VREL + ((seq + 1) & 3)) * 8, lane);
          TSTAMP(2 + it * 20 + t);
        };
#pragma unroll 1
        for (int t = 0; t < NKT - 1; t++) pv_step(t, false);
        pv_step(NKT - 1, true);
        uint32_t ui0, ui1;
        asm volatile("ld.shared.v2.b32 {%0, %1}, [%2];" : "=r"(ui0), "=r"(ui1) : "r"(mstat + pstage * PMSG_W + 8) : "memory");
        if (rel == 11) issue_ring(m, seq - 1 + NS_O, sbase, b0, h, 1);
        const float i0 = __uint_as_float(ui0), i1 = __uint_as_float(ui1);
#pragma unroll
        for (int j = 31; j >= 0; j--) {
          of[2 * j + 1] = pack_bf16_v(o[4 * j + 2] * i1, o[4 * j + 3] * i1);
          of[2 * j] = pack_bf16_v(o[4 * j] * i0, o[4 * j + 1] * i0);
        }
        __syncwarp();
        if (lane == 0) {
          mbar_expect_tx(pfull + pstage * 8, PMSG_W);
          mbar_arrive_remote(pempty_r + pstage * 8);
        }
        if (++pstage == PST) { pstage = 0; pphase ^= 1; }
      }
      if (it == 0) {
        mbar_wait(bars + BAR_XFREE * 8, 1);
#pragma unroll
        for (int j = 0; j < 16; j++) st_async_v4(xbuf_r + j * 512, of[4 * j], of[4 * j + 1], of[4 * j + 2], of[4 * j + 3], xf_r);
        TSTAMP(18);
      } else {
        oproj(of);
      }
    }
  }
  __threadfence();
  __syncwarp();
  if (lane == 0) atomicAdd(g_cnt + rank, 1u);
  TSTAMP(39);
  {
    uint4 va[NH], vb[NH];
    if (rank == 0) {
      wait_all(tid, 0);
      const int u = cl * 12 + warp;
      const bool two = u + 768 < 4 * SLICES_PER_B;
      slice_load(u, lane, va);
      if (two) slice_load(u + 768, lane, vb);
      slice_store(u, lane, va, out);
      if (two) slice_store(u + 768, lane, vb, out);
      TSTAMP(38);
    }
    wait_all(tid, 1);
    TSTAMP(40);
    const int u = blockIdx.x * 12 + warp;
    if (u < 4 * SLICES_PER_B) {
      slice_load(4 * SLICES_PER_B + u, lane, va);
      slice_store(4 * SLICES_PER_B + u, lane, va, out);
    }
    __syncwarp();
    if (lane == 0) {
      if (atomicAdd(g_done, 1u) == 128 * 12 - 1) { g_cnt[0] = 0; g_cnt[1] = 0; g_done[0] = 0; }
    }
    TSTAMP(41);
  }
  TSTAMP(63);
  TS_GT(1);
  TS_END();
  __syncwarp();
  cluster_sync_all();
  TS_GT(3);
}

typedef CUresult (*PFN_encodeTiled)(CUtensorMap*, CUtensorMapDataType, cuuint32_t, void*, const cuuint64_t*, const cuuint64_t*,
                                    const cuuint32_t*, const cuuint32_t*, CUtensorMapInterleave, CUtensorMapSwizzle,
                                    CUtensorMapL2promotion, CUtensorMapFloatOOBfill);

void encode(PFN_encodeTiled fn, CUtensorMap* m, int rank, const void* ptr, const cuuint64_t* dims, const cuuint64_t* strides,
            const cuuint32_t* box) {
  cuuint32_t es[3] = {1, 1, 1};
  fn(m, CU_TENSOR_MAP_DATA_TYPE_BFLOAT16, (cuuint32_t)rank, const_cast<void*>(ptr), dims, strides, box, es,
     CU_TENSOR_MAP_INTERLEAVE_NONE, CU_TENSOR_MAP_SWIZZLE_128B, CU_TENSOR_MAP_L2_PROMOTION_L2_256B,
     CU_TENSOR_MAP_FLOAT_OOB_FILL_NONE);
}

}

extern "C" void kernel_launch(void* const* d_in, const int* in_sizes, int n_in, void* d_out, int out_size) {
  const void* x = d_in[0];
  const void* kc = d_in[1];
  const void* vc = d_in[2];
  const void* wq = d_in[3];
  const void* wo = d_in[4];

  static PFN_encodeTiled fn = nullptr;
  if (!fn) {
    void* p = nullptr;
    cudaDriverEntryPointQueryResult qr;
    cudaGetDriverEntryPoint("cuTensorMapEncodeTiled", &p, cudaEnableDefault, &qr);
    fn = (PFN_encodeTiled)p;
    cudaFuncSetAttribute(mha_kernel, cudaFuncAttributeMaxDynamicSharedMemorySize, SMEM_BYTES + TS_EXTRA);
  }
  CUtensorMap tm_x, tm_wq, tm_k, tm_v, tm_wo;
  {
    cuuint64_t dims[2] = {DM, (cuuint64_t)NB * SQ};
    cuuint64_t str[1] = {DM * 2};
    cuuint32_t box[2] = {64, SQ};
    encode(fn, &tm_x, 2, x, dims, str, box);
  }
  {
    cuuint64_t dims[3] = {64, DM, (cuuint64_t)NH * DH / 64};
    cuuint64_t str[2] = {(cuuint64_t)NH * DH * 2, 128};
    cuuint32_t box[3] = {64, 64, 4};
    encode(fn, &tm_wq, 3, wq, dims, str, box);
  }
  {
    cuuint64_t dims[3] = {64, (cuuint64_t)NB * NH * SK, 4};
    cuuint64_t str[2] = {DH * 2, 128};
    cuuint32_t box[3] = {64, 64, 4};
    encode(fn, &tm_k, 3, kc, dims, str, box);
    encode(fn, &tm_v, 3, vc, dims, str, box);
  }
  {
    cuuint64_t dims[2] = {DM, (cuuint64_t)NH * DH};
    cuuint64_t str[1] = {DM * 2};
    cuuint32_t box[2] = {64, DH};
    encode(fn, &tm_wo, 2, wo, dims, str, box);
  }
  mha_kernel<<<128, 384, SMEM_BYTES + TS_EXTRA>>>(tm_x, tm_wq, tm_k, tm_v, tm_wo, (const __nv_bfloat16*)kc, (const __nv_bfloat16*)vc,
                                       (const __nv_bfloat16*)x, (const __nv_bfloat16*)wo, (__nv_bfloat16*)d_out);
}
```

```cpp
#include <cuda_runtime.h>
#include <cuda_bf16.h>
#include <cuda.h>
#include <stdint.h>
#include <type_traits>

namespace {

constexpr int NB = 8, SQ = 192, DM = 448, NH = 16, SK = 1024, DH = 256;
constexpr int SLOT = 32768;
constexpr int NS_O = 4;
constexpr int PST = 3;
constexpr int PMSG_W = 2176;
constexpr int NKT = SK / 64;
constexpr int NKC = DM / 64;
constexpr int PF_K0 = 1, PF_HEAD = 3;

constexpr int OFF_MBOX = NS_O * SLOT;
constexpr int OFF_XBUF = 2 * 2 * SLOT;
constexpr int OFF_BAR = OFF_XBUF + 3 * SLOT;
static_assert(OFF_BAR >= OFF_MBOX + 12 * PST * PMSG_W, "smem layout");
constexpr int BAR_SF = 0;
constexpr int BAR_VF = 4;
constexpr int BAR_SREL = 8;
constexpr int BAR_VREL = 12;
constexpr int BAR_XFREE = 16;
constexpr int BAR_XF = 17;
constexpr int BAR_P = 20;
constexpr int NBARS = BAR_P + 12 * PST;
constexpr int SMEM_BYTES = OFF_BAR + NBARS * 8 + 1024;

constexpr int SLICES_PER_B = NKC * 3 * 4 * 4;

__device__ uint4 g_part[(size_t)NB * NH * NKC * 3 * 4 * 128];
__device__ unsigned int g_cnt[2];
__device__ unsigned int g_done[1];

__device__ __forceinline__ uint32_t smem_u32(const void* p) { return (uint32_t)__cvta_generic_to_shared(p); }

__device__ __forceinline__ void mbar_init(uint32_t bar, uint32_t cnt) {
  asm volatile("mbarrier.init.shared::cta.b64 [%0], %1;" ::"r"(bar), "r"(cnt) : "memory");
}
__device__ __forceinline__ void mbar_expect_tx(uint32_t bar, uint32_t bytes) {
  asm volatile("mbarrier.arrive.expect_tx.shared::cta.b64 _, [%0], %1;" ::"r"(bar), "r"(bytes) : "memory");
}
__device__ __forceinline__ void mbar_arrive_remote(uint32_t rbar) {
  asm volatile("mbarrier.arrive.shared::cluster.b64 _, [%0];" ::"r"(rbar) : "memory");
}
constexpr uint32_t SPIN_LIMIT = 1u << 22;
__device__ __forceinline__ void mbar_wait(uint32_t bar, uint32_t parity) {
  asm volatile(
      "{\n.reg .pred p, q;\n.reg .u32 n;\n"
      "mbarrier.try_wait.parity.shared::cta.b64 p, [%0], %1;\n"
      "@p bra.uni DONE_%=;\n"
      "mov.u32 n, 0;\n"
      "LOOP_%=:\n"
      "mbarrier.try_wait.parity.shared::cta.b64 p, [%0], %1;\n"
      "@p bra.uni DONE_%=;\n"
      "add.u32 n, n, 1;\n"
      "setp.lt.u32 q, n, 4194304;\n"
      "@q bra.uni LOOP_%=;\n"
      "trap;\n"
      "DONE_%=:\n}"
      ::"r"(bar), "r"(parity) : "memory");
}
__device__ __forceinline__ uint32_t mapa(uint32_t addr, uint32_t rank) {
  uint32_t r;
  asm volatile("mapa.shared::cluster.u32 %0, %1, %2;" : "=r"(r) : "r"(addr), "r"(rank));
  return r;
}
__device__ __forceinline__ void tma_2d(uint32_t dst, const CUtensorMap* tm, int c0, int c1, uint32_t bar) {
  asm volatile("cp.async.bulk.tensor.2d.shared::cluster.global.mbarrier::complete_tx::bytes [%0], [%1, {%3, %4}], [%2];"
               ::"r"(dst), "l"(tm), "r"(bar), "r"(c0), "r"(c1) : "memory");
}
__device__ __forceinline__ void tma_3d(uint32_t dst, const CUtensorMap* tm, int c0, int c1, int c2, uint32_t bar) {
  asm volatile("cp.async.bulk.tensor.3d.shared::cluster.global.mbarrier::complete_tx::bytes [%0], [%1, {%3, %4, %5}], [%2];"
               ::"r"(dst), "l"(tm), "r"(bar), "r"(c0), "r"(c1), "r"(c2) : "memory");
}
__device__ __forceinline__ void tma_3d_ef(uint32_t dst, const CUtensorMap* tm, int c0, int c1, int c2, uint32_t bar) {
  asm volatile("{\n.reg .b64 pol;\ncreatepolicy.fractional.L2::evict_first.b64 pol, 1.0;\n"
               "cp.async.bulk.tensor.3d.shared::cluster.global.mbarrier::complete_tx::bytes.L2::cache_hint [%0], [%1, {%3, %4, %5}], [%2], pol;\n}"
               ::"r"(dst), "l"(tm), "r"(bar), "r"(c0), "r"(c1), "r"(c2) : "memory");
}
__device__ __forceinline__ void l2_prefetch(const void* p, uint32_t bytes) {
  asm volatile("cp.async.bulk.prefetch.L2.global [%0], %1;" ::"l"(p), "r"(bytes) : "memory");
}
__device__ __forceinline__ void st_async_v4(uint32_t raddr, uint32_t a, uint32_t b, uint32_t c, uint32_t d, uint32_t rbar) {
  asm volatile("st.async.weak.shared::cluster.mbarrier::complete_tx::bytes.v4.b32 [%0], {%1, %2, %3, %4}, [%5];"
               ::"r"(raddr), "r"(a), "r"(b), "r"(c), "r"(d), "r"(rbar) : "memory");
}
__device__ __forceinline__ void lds_v4(uint32_t addr, uint32_t& a, uint32_t& b, uint32_t& c, uint32_t& d) {
  asm volatile("ld.shared.v4.b32 {%0, %1, %2, %3}, [%4];" : "=r"(a), "=r"(b), "=r"(c), "=r"(d) : "r"(addr) : "memory");
}
__device__ __forceinline__ uint32_t pack_bf16(float lo, float hi) {
  uint32_t r;
  asm("cvt.rn.bf16x2.f32 %0, %1, %2;" : "=r"(r) : "f"(hi), "f"(lo));
  return r;
}
__device__ __forceinline__ uint32_t pack_bf16_v(float lo, float hi) {
  uint32_t r;
  asm volatile("cvt.rn.bf16x2.f32 %0, %1, %2;" : "=r"(r) : "f"(hi), "f"(lo));
  return r;
}
__device__ __forceinline__ float ex2v(float x) {
  float r;
  asm volatile("ex2.approx.ftz.f32 %0, %1;" : "=f"(r) : "f"(x));
  return r;
}
__device__ __forceinline__ float ex2(float x) {
  float r;
  asm("ex2.approx.ftz.f32 %0, %1;" : "=f"(r) : "f"(x));
  return r;
}

__device__ __forceinline__ uint64_t make_desc(uint32_t addr, uint32_t lbo, uint32_t sbo) {
  return (uint64_t)((addr & 0x3FFFF) >> 4) | ((uint64_t)(lbo >> 4) << 16) | ((uint64_t)(sbo >> 4) << 32) | (1ull << 62);
}
__device__ __forceinline__ void wg_fence() { asm volatile("wgmma.fence.sync.aligned;" ::: "memory"); }
__device__ __forceinline__ void wg_commit() { asm volatile("wgmma.commit_group.sync.aligned;" ::: "memory"); }
template <int N> __device__ __forceinline__ void wg_wait() { asm volatile("wgmma.wait_group.sync.aligned %0;" ::"n"(N) : "memory"); }
template <int N> __device__ __forceinline__ void fence_regs(float (&r)[N]) {
#pragma unroll
  for (int i = 0; i < N; i++) asm volatile("" : "+f"(r[i])::"memory");
}

#define F8(a, o) "+f"(a[o + 0]), "+f"(a[o + 1]), "+f"(a[o + 2]), "+f"(a[o + 3]), "+f"(a[o + 4]), "+f"(a[o + 5]), "+f"(a[o + 6]), "+f"(a[o + 7])
#define F32(a, o) F8(a, o), F8(a, o + 8), F8(a, o + 16), F8(a, o + 24)
#define F128(a) F32(a, 0), F32(a, 32), F32(a, 64), F32(a, 96)
#define D32 "{%0, %1, %2, %3, %4, %5, %6, %7, %8, %9, %10, %11, %12, %13, %14, %15, %16, %17, %18, %19, %20, %21, %22, %23, %24, %25, %26, %27, %28, %29, %30, %31}"
#define D128 "{%0, %1, %2, %3, %4, %5, %6, %7, %8, %9, %10, %11, %12, %13, %14, %15, %16, %17, %18, %19, %20, %21, %22, %23, %24, %25, %26, %27, %28, %29, %30, %31, " \
  "%32, %33, %34, %35, %36, %37, %38, %39, %40, %41, %42, %43, %44, %45, %46, %47, %48, %49, %50, %51, %52, %53, %54, %55, %56, %57, %58, %59, %60, %61, %62, %63, " \
  "%64, %65, %66, %67, %68, %69, %70, %71, %72, %73, %74, %75, %76, %77, %78, %79, %80, %81, %82, %83, %84, %85, %86, %87, %88, %89, %90, %91, %92, %93, %94, %95, " \
  "%96, %97, %98, %99, %100, %101, %102, %103, %104, %105, %106, %107, %108, %109, %110, %111, %112, %113, %114, %115, %116, %117, %118, %119, %120, %121, %122, %123, %124, %125, %126, %127}"

__device__ __forceinline__ void wgmma_n256_ss(float (&d)[128], uint64_t da, uint64_t db, int scale_d) {
  asm volatile("{\n.reg .pred p;\nsetp.ne.b32 p, %130, 0;\n"
               "wgmma.mma_async.sync.aligned.m64n256k16.f32.bf16.bf16 " D128 ", %128, %129, p, 1, 1, 0, 1;\n}"
               : F128(d) : "l"(da), "l"(db), "r"(scale_d));
}
__device__ __forceinline__ void wgmma_n256_rs(float (&d)[128], uint32_t a0, uint32_t a1, uint32_t a2, uint32_t a3, uint64_t db, int scale_d) {
  asm volatile("{\n.reg .pred p;\nsetp.ne.b32 p, %133, 0;\n"
               "wgmma.mma_async.sync.aligned.m64n256k16.f32.bf16.bf16 " D128 ", {%128, %129, %130, %131}, %132, p, 1, 1, 1;\n}"
               : F128(d) : "r"(a0), "r"(a1), "r"(a2), "r"(a3), "l"(db), "r"(scale_d));
}
template <int TB>
__device__ __forceinline__ void wgmma_n64_rs(float (&d)[32], uint32_t a0, uint32_t a1, uint32_t a2, uint32_t a3, uint64_t db, int scale_d) {
  asm volatile("{\n.reg .pred p;\nsetp.ne.b32 p, %37, 0;\n"
               "wgmma.mma_async.sync.aligned.m64n64k16.f32.bf16.bf16 " D32 ", {%32, %33, %34, %35}, %36, p, 1, 1, %38;\n}"
               : F32(d, 0) : "r"(a0), "r"(a1), "r"(a2), "r"(a3), "l"(db), "r"(scale_d), "n"(TB));
}

__device__ __forceinline__ void token_wait(int wg) { asm volatile("bar.sync %0, 256;" ::"r"(wg + 1) : "memory"); }
__device__ __forceinline__ void token_pass(int wg) { asm volatile("bar.arrive %0, 256;" ::"r"(wg == 2 ? 1 : wg + 2) : "memory"); }

__device__ __forceinline__ void slice_load(int s, int lane, uint4 (&v)[NH]) {
  const int b = s / SLICES_PER_B, r = s % SLICES_PER_B;
  const uint4* src = g_part + ((size_t)b * NH * NKC * 3 * 4 * 128 + (size_t)r * 32 + lane);
  constexpr size_t HSTRIDE = (size_t)NKC * 3 * 4 * 128;
#pragma unroll
  for (int i = 0; i < NH; i++) v[i] = __ldcg(src + (size_t)i * HSTRIDE);
}
__device__ __forceinline__ void slice_store(int s, int lane, const uint4 (&v)[NH], __nv_bfloat16* out) {
  const int b = s / SLICES_PER_B, r = s % SLICES_PER_B;
  const int warp = r & 3, j = (r >> 2) & 3, cw = r >> 4;
  const int w = cw % 3, c = cw / 3;
  float acc[8];
#pragma unroll
  for (int i = 0; i < 8; i++) acc[i] = 0.f;
#pragma unroll
  for (int i = 0; i < NH; i++) {
    acc[0] += __uint_as_float(v[i].x << 16); acc[1] += __uint_as_float(v[i].x & 0xffff0000u);
    acc[2] += __uint_as_float(v[i].y << 16); acc[3] += __uint_as_float(v[i].y & 0xffff0000u);
    acc[4] += __uint_as_float(v[i].z << 16); acc[5] += __uint_as_float(v[i].z & 0xffff0000u);
    acc[6] += __uint_as_float(v[i].w << 16); acc[7] += __uint_as_float(v[i].w & 0xffff0000u);
  }
  const int g = lane >> 2, q = lane & 3;
  const int row = w * 64 + warp * 16 + g;
  const int col = c * 64 + j * 16 + 2 * q;
  uint32_t* o = reinterpret_cast<uint32_t*>(out + ((size_t)(b * SQ + row) * DM + col));
  o[0] = pack_bf16(acc[0], acc[1]);
  o[8 * DM / 2] = pack_bf16(acc[2], acc[3]);
  o[4] = pack_bf16(acc[4], acc[5]);
  o[8 * DM / 2 + 4] = pack_bf16(acc[6], acc[7]);
}

__device__ __forceinline__ void wait_all(int tid, int idx) {
  if (tid == 0) {
    uint32_t n = 0;
    while (true) {
      unsigned int v;
      asm volatile("ld.acquire.gpu.global.u32 %0, [%1];" : "=r"(v) : "l"(g_cnt + idx) : "memory");
      if (v >= 64u * 12u) break;
      __nanosleep(20);
      if (++n > SPIN_LIMIT) __trap();
    }
  }
  asm volatile("bar.sync 4, 384;" ::: "memory");
}

struct Maps {
  const CUtensorMap *x, *wq, *k, *v, *wo;
  const char *kptr, *vptr, *xptr;
};
__device__ __forceinline__ void load_chunk(const Maps& m, int c, uint32_t sbase, int b, int h) {
  const uint32_t stage = c % 3;
  const uint32_t dst = sbase + stage * (2 * SLOT);
  const uint32_t bar = sbase + OFF_BAR + (BAR_SF + stage) * 8;
  mbar_expect_tx(bar, SLOT + SQ * 128);
  tma_2d(dst, m.x, c * 64, b * SQ, bar);
  tma_3d(dst + SLOT, m.wq, 0, c * 64, h * 4, bar);
}
__device__ __forceinline__ void issue_ring(const Maps& m, int n, uint32_t sbase, int b0, int h, uint32_t rank) {
  if (n >= 2 * NKT + NKC) return;
  const uint32_t slot = (n + 2) & 3;
  const uint32_t dst = sbase + slot * SLOT;
  const uint32_t bar = sbase + OFF_BAR + (BAR_VF + slot) * 8;
  mbar_expect_tx(bar, SLOT);
  if (n < 2 * NKT) tma_3d_ef(dst, rank ? m.v : m.k, 0, ((b0 + 4 * (n >> 4)) * NH + h) * SK + (n & 15) * 64, 0, bar);
  else tma_2d(dst, m.wo, (n - 2 * NKT) * 64, h * DH, bar);
}
__device__ __forceinline__ void store_chunk(uint4* dst, const float (&a)[32]) {
#pragma unroll
  for (int j = 0; j < 4; j++) {
    uint4 w;
    w.x = pack_bf16(a[8 * j], a[8 * j + 1]);
    w.y = pack_bf16(a[8 * j + 2], a[8 * j + 3]);
    w.z = pack_bf16(a[8 * j + 4], a[8 * j + 5]);
    w.w = pack_bf16(a[8 * j + 6], a[8 * j + 7]);
    dst[j * 128] = w;
  }
}
__device__ __forceinline__ void pf_tile(const Maps& m, int b0, int h, int it, int kv, int j) {
  if (j < NKT) l2_prefetch((kv ? m.vptr : m.kptr) + ((size_t)((b0 + 4 * it) * NH + h) * NKT + j) * SLOT, SLOT);
}

__device__ __forceinline__ uint32_t release_slot(uint32_t cnt_addr, int lane) {
  uint32_t old = 0;
  if (lane == 0) asm volatile("atom.relaxed.cta.shared.inc.u32 %0, [%1], 11;" : "=r"(old) : "r"(cnt_addr) : "memory");
  return old;
}

__global__ void __cluster_dims__(2, 1, 1) __launch_bounds__(384, 1)
mha_kernel(const __grid_constant__ CUtensorMap tm_x, const __grid_constant__ CUtensorMap tm_wq,
           const __grid_constant__ CUtensorMap tm_k, const __grid_constant__ CUtensorMap tm_v,
           const __grid_constant__ CUtensorMap tm_wo, const __nv_bfloat16* __restrict__ kptr,
           const __nv_bfloat16* __restrict__ vptr, const __nv_bfloat16* __restrict__ xptr,
           const __nv_bfloat16* __restrict__ wqptr, __nv_bfloat16* __restrict__ out) {
  extern __shared__ uint8_t smem_raw[];
  const uint32_t sbase = (smem_u32(smem_raw) + 1023u) & ~1023u;
  const uint32_t bars = sbase + OFF_BAR;
  const int tid = threadIdx.x;
  const int warp = __shfl_sync(0xffffffffu, tid >> 5, 0), lane = tid & 31;
  const int wg = warp >> 2;
  uint32_t rank;
  asm volatile("mov.u32 %0, %%cluster_ctarank;" : "=r"(rank));
  const int cl = blockIdx.x >> 1;
  const int h = cl & 15;
  const int b0 = cl >> 4;

  Maps m{&tm_x, &tm_wq, &tm_k, &tm_v, &tm_wo, reinterpret_cast<const char*>(kptr), reinterpret_cast<const char*>(vptr),
         reinterpret_cast<const char*>(xptr)};
  if (tid == 0) {
    for (int i = 0; i < 8; i++) {
      mbar_init(bars + i * 8, 1);
      asm volatile("st.shared.u32 [%0], 0;" ::"r"(bars + (BAR_SREL + i) * 8) : "memory");
    }
    asm volatile("fence.mbarrier_init.release.cluster;" ::: "memory");
    asm volatile("fence.proxy.async.shared::cta;" ::: "memory");
    for (int i = 0; i < 3; i++) load_chunk(m, i, sbase, b0 + 4 * rank, h);
  } else if (tid == 32) {
    mbar_init(bars + BAR_XFREE * 8, 1);
    mbar_init(bars + BAR_XF * 8, 1);
    for (int i = 0; i < 12 * PST; i++) mbar_init(bars + (BAR_P + i) * 8, 1);
    if (rank == 1) {
      for (int i = 0; i < 12 * PST; i++) mbar_expect_tx(bars + (BAR_P + i) * 8, PMSG_W);
    } else {
      mbar_expect_tx(bars + BAR_XF * 8, 3 * SLOT);
    }
    asm volatile("fence.mbarrier_init.release.cluster;" ::: "memory");
  }
  __syncthreads();
  asm volatile("barrier.cluster.arrive.relaxed.aligned;\nbarrier.cluster.wait.aligned;" ::: "memory");

  uint32_t sph = 0;
  uint32_t q[64];
  {
    float acc[128];
#pragma unroll
    for (int i = 0; i < 128; i++) acc[i] = 0.f;
    auto after_chunk = [&](int c) {
      if (c < 4) load_chunk(m, c + 3, sbase, b0 + 4 * rank, h);
      else if (c == 5) {
        if (rank == 0) mbar_arrive_remote(mapa(bars + BAR_XFREE * 8, 1));
      } else {
        issue_ring(m, c - 4, sbase, b0, h, rank);
        issue_ring(m, c - 3, sbase, b0, h, rank);
      }
    };
    uint32_t st = 0, prev = 0;
#pragma unroll 1
    for (int kc = 0; kc < NKC; kc++) {
      mbar_wait(bars + (BAR_SF + st) * 8, (sph >> st) & 1);
      sph ^= 1u << st;
      const uint64_t da = make_desc(sbase + st * (2 * SLOT) + wg * 8192, 16, 1024);
      const uint64_t db = make_desc(sbase + st * (2 * SLOT) + SLOT, 8192, 1024);
      wg_fence();
#pragma unroll
      for (int ks = 0; ks < 4; ks++) wgmma_n256_ss(acc, da + ks * 2, db + ks * 128, (kc | ks) != 0);
      wg_commit();
      if (kc == 0 && tid == 320) {
        l2_prefetch(reinterpret_cast<const char*>(wqptr) + (size_t)192 * NH * DH * 2 + (size_t)blockIdx.x * (256 * NH * DH * 2 / 128), 256 * NH * DH * 2 / 128);
        l2_prefetch(m.xptr + (size_t)blockIdx.x * (NB * SQ * DM * 2 / 128), NB * SQ * DM * 2 / 128);
      }
      if (rank == 0 && (tid & 127) == 64 && wg < 2 && kc >= PF_K0 && kc < PF_K0 + PF_HEAD) pf_tile(m, b0, h, 0, wg, kc - PF_K0);
      if (kc > 0) {
        wg_wait<1>();
        if (release_slot(bars + (BAR_SREL + prev) * 8, lane) == 11) after_chunk(kc - 1);
      }
      prev = st;
      st = st == 2 ? 0 : st + 1;
    }
    wg_wait<0>();
    fence_regs(acc);
    if (release_slot(bars + (BAR_SREL + prev) * 8, lane) == 11) after_chunk(NKC - 1);
#pragma unroll
    for (int i = 63; i >= 0; i--) q[i] = pack_bf16_v(acc[2 * i], acc[2 * i + 1]);
  }

  int seq = 0;
  auto oproj = [&](uint32_t (&of)[64]) {
    uint32_t tid2;
    asm volatile("mov.u32 %0, %%tid.x;" : "=r"(tid2));
    uint4* dst = g_part + ((size_t)((b0 + 4 * rank) * NH + h) * NKC * 3 * 4 * 128 + (size_t)wg * 4 * 128 + (tid2 & 127));
    float acc[2][32];
#pragma unroll
    for (int i = 0; i < 32; i++) { acc[0][i] = 0.f; acc[1][i] = 0.f; }
#pragma unroll
    for (int c = 0; c <= NKC; c++) {
      constexpr int n0 = 2 * NKT;
      if (c < NKC) {
        const uint32_t slot = (n0 + c + 2) & 3;
        mbar_wait(bars + (BAR_VF + slot) * 8, ((n0 + c) >> 2) & 1);
        uint32_t sb2;
        asm volatile("mov.u32 %0, %1;" : "=r"(sb2) : "r"(sbase));
        const uint64_t db = make_desc(sb2 + slot * SLOT, 8192, 1024);
        wg_fence();
#pragma unroll
        for (int ks = 0; ks < 16; ks++)
          wgmma_n64_rs<1>(acc[c & 1], of[4 * ks], of[4 * ks + 1], of[4 * ks + 2], of[4 * ks + 3], db + ks * 128, ks != 0);
        wg_commit();
      }
      if (c > 0) {
        if (c < NKC) wg_wait<1>(); else wg_wait<0>();
        float(&a)[32] = acc[(c - 1) & 1];
        fence_regs(a);
        uint32_t rel = 0;
        if (c - 1 + NS_O < NKC) rel = release_slot(bars + (BAR_VREL + ((n0 + c + 1) & 3)) * 8, lane);
        store_chunk(dst + (size_t)(c - 1) * (3 * 4 * 128), a);
        if (rel == 11) issue_ring(m, n0 + c - 1 + NS_O, sbase, b0, h, rank);
      }
    }
  };
  if (rank == 0) {
    uint32_t pstage = 0, pphase = 0;
    const uint32_t mbox_r = mapa(sbase + OFF_MBOX + warp * (PST * PMSG_W) + lane * 16, 1);
    const uint32_t pfull_r = mapa(bars + (BAR_P + warp * PST) * 8, 1);
    const uint32_t pempty = bars + (BAR_P + warp * PST) * 8;
    const uint32_t xbuf = sbase + OFF_XBUF + warp * 8192 + lane * 16;
    const float cs = 0.0625f * 1.4426950408889634f;
#pragma unroll 1
    for (int it = 0; it < 2; it++) {
      if (it == 1) {
        mbar_wait(bars + BAR_XF * 8, 0);
#pragma unroll
        for (int j = 0; j < 16; j++) lds_v4(xbuf + j * 512, q[4 * j], q[4 * j + 1], q[4 * j + 2], q[4 * j + 3]);
      }
      float n0 = INFINITY, n1 = INFINITY, l0 = 0.f, l1 = 0.f;
      float sA[32], sB[32];
#pragma unroll
      for (int i = 0; i < 32; i++) { sA[i] = 0.f; sB[i] = 0.f; }
      float a0 = 1.f, a1 = 1.f;
      auto new_ref = [&](float (&s)[32]) {
        float mx0 = fmaxf(s[0], s[1]), mx1 = fmaxf(s[2], s[3]);
#pragma unroll
        for (int j = 1; j < 8; j++) {
          mx0 = fmaxf(mx0, fmaxf(s[4 * j], s[4 * j + 1]));
          mx1 = fmaxf(mx1, fmaxf(s[4 * j + 2], s[4 * j + 3]));
        }
        mx0 = fmaxf(mx0, __shfl_xor_sync(0xffffffffu, mx0, 1));
        mx1 = fmaxf(mx1, __shfl_xor_sync(0xffffffffu, mx1, 1));
        mx0 = fmaxf(mx0, __shfl_xor_sync(0xffffffffu, mx0, 2));
        mx1 = fmaxf(mx1, __shfl_xor_sync(0xffffffffu, mx1, 2));
        const float n0n = fminf(n0, -mx0 * cs), n1n = fminf(n1, -mx1 * cs);
        a0 = ex2(n0n - n0); a1 = ex2(n1n - n1);
        n0 = n0n; n1 = n1n;
        l0 *= a0; l1 *= a1;
      };
      auto step = [&](float (&s)[32], float (&sn)[32], uint64_t db, auto mma_tag, bool fresh_ref, bool last) {
        constexpr bool MMA = decltype(mma_tag)::value;
        mbar_wait(pempty + pstage * 8, pphase);
        uint32_t dst = mbox_r + pstage * PMSG_W;
        uint32_t rb = pfull_r + pstage * 8;
        float s0 = 0.f, s1 = 0.f;
        uint32_t p[4];
        if (MMA) wg_fence();
#pragma unroll
        for (int ks = 0; ks < 16; ks++) {
          if (MMA)
            wgmma_n64_rs<0>(sn, q[4 * ks], q[4 * ks + 1], q[4 * ks + 2], q[4 * ks + 3], db + (ks >> 2) * 512 + (ks & 3) * 2, ks != 0);
          const float nn = (ks & 1) ? n1 : n0;
          const float e0 = ex2v(fmaf(s[2 * ks], cs, nn)), e1 = ex2v(fmaf(s[2 * ks + 1], cs, nn));
          if (ks & 1) s1 += e0 + e1; else s0 += e0 + e1;
          p[ks & 3] = pack_bf16(e0, e1);
          if ((ks & 3) == 3) st_async_v4(dst + (ks >> 2) * 512, p[0], p[1], p[2], p[3], rb);
        }
        if (MMA) wg_commit();
        if (!fresh_ref && __any_sync(0xffffffffu, !(s0 <= 1048576.f) || !(s1 <= 1048576.f))) {
          if ((lane & 3) == 0) st_async_v4(dst + 2048 - lane * 12, 0xbf800000u, 0u, 0u, 0u, rb);
          if (++pstage == PST) { pstage = 0; pphase ^= 1; }
          new_ref(s);
          mbar_wait(pempty + pstage * 8, pphase);
          dst = mbox_r + pstage * PMSG_W;
          rb = pfull_r + pstage * 8;
          s0 = 0.f; s1 = 0.f;
#pragma unroll
          for (int ks = 0; ks < 16; ks++) {
            const float nn = (ks & 1) ? n1 : n0;
            const float e0 = ex2(fmaf(s[2 * ks], cs, nn)), e1 = ex2(fmaf(s[2 * ks + 1], cs, nn));
            if (ks & 1) s1 += e0 + e1; else s0 += e0 + e1;
            p[ks & 3] = pack_bf16(e0, e1);
            if ((ks & 3) == 3) st_async_v4(dst + (ks >> 2) * 512, p[0], p[1], p[2], p[3], rb);
          }
        }
        l0 += s0; l1 += s1;
        float i0 = 0.f, i1 = 0.f;
        if (last) {
          float t0 = l0 + __shfl_xor_sync(0xffffffffu, l0, 1);
          float t1 = l1 + __shfl_xor_sync(0xffffffffu, l1, 1);
          t0 += __shfl_xor_sync(0xffffffffu, t0, 2);
          t1 += __shfl_xor_sync(0xffffffffu, t1, 2);
          i0 = __frcp_rn(t0); i1 = __frcp_rn(t1);
        }
        if ((lane & 3) == 0)
          st_async_v4(dst + 2048 - lane * 12, __float_as_uint(a0), __float_as_uint(a1), __float_as_uint(i0), __float_as_uint(i1), rb);
        a0 = 1.f; a1 = 1.f;
        if (++pstage == PST) { pstage = 0; pphase ^= 1; }
      };
      auto kdesc = [&]() {
        const uint32_t slot = (seq + 2) & 3;
        mbar_wait(bars + (BAR_VF + slot) * 8, (seq >> 2) & 1);
        return make_desc(sbase + slot * SLOT, 16, 1024);
      };
      auto kdone = [&]() {
        if (release_slot(bars + (BAR_VREL + ((seq + 2) & 3)) * 8, lane) == 11) issue_ring(m, seq + NS_O, sbase, b0, h, 0);
        __syncwarp();
        seq++;
      };
      {
        const uint64_t db = kdesc();
        wg_fence();
#pragma unroll
        for (int ks = 0; ks < 16; ks++)
          wgmma_n64_rs<0>(sA, q[4 * ks], q[4 * ks + 1], q[4 * ks + 2], q[4 * ks + 3], db + (ks >> 2) * 512 + (ks & 3) * 2, ks != 0);
        wg_commit();
        if (it == 1 && release_slot(bars + (BAR_SREL + 2) * 8, lane) == 11) {
          mbar_expect_tx(bars + BAR_XF * 8, 3 * SLOT);
          mbar_arrive_remote(mapa(bars + BAR_XFREE * 8, 1));
        }
        wg_wait<0>();
        fence_regs(sA);
        kdone();
        new_ref(sA);
      }
#pragma unroll 1
      for (int t = 0; t < NKT; t += 2) {
        step(sA, sB, kdesc(), std::true_type{}, t == 0, false);
        wg_wait<0>();
        fence_regs(sB);
        kdone();
        if (t + 2 < NKT) {
          step(sB, sA, kdesc(), std::true_type{}, false, false);
          wg_wait<0>();
          fence_regs(sA);
          kdone();
        } else {
          step(sB, sA, 0, std::false_type{}, false, true);
        }
      }
    }
    uint32_t of[64];
    mbar_wait(bars + BAR_XF * 8, 1);
#pragma unroll
    for (int j = 0; j < 16; j++) lds_v4(xbuf + j * 512, of[4 * j], of[4 * j + 1], of[4 * j + 2], of[4 * j + 3]);
    oproj(of);
  } else {
    uint32_t pstage = 0, pphase = 0;
    const uint32_t mbox = sbase + OFF_MBOX + warp * (PST * PMSG_W) + lane * 16;
    const uint32_t mstat = sbase + OFF_MBOX + warp * (PST * PMSG_W) + 2048 + (lane >> 2) * 16;
    const uint32_t pfull = bars + (BAR_P + warp * PST) * 8;
    const uint32_t pempty_r = mapa(bars + (BAR_P + warp * PST) * 8, 0);
    const uint32_t xbuf_r = mapa(sbase + OFF_XBUF + warp * 8192 + lane * 16, 0);
    const uint32_t xf_r = mapa(bars + BAR_XF * 8, 0);
    {
      asm volatile("bar.sync 4, 384;" ::: "memory");
      if (lane < PST) mbar_arrive_remote(pempty_r + lane * 8);
      __syncwarp();
      mbar_wait(bars + BAR_XFREE * 8, 0);
#pragma unroll
      for (int j = 0; j < 16; j++) st_async_v4(xbuf_r + j * 512, q[4 * j], q[4 * j + 1], q[4 * j + 2], q[4 * j + 3], xf_r);
      if (wg == 2) token_pass(2);
    }
#pragma unroll 1
    for (int it = 0; it < 2; it++) {
      uint32_t of[64];
      {
        float o[128];
#pragma unroll
        for (int i = 0; i < 128; i++) o[i] = 0.f;
        uint32_t ua0 = 0x3f800000u, ua1 = 0x3f800000u;
        mbar_wait(pfull + pstage * 8, pphase);
        mbar_wait(bars + (BAR_VF + ((seq + 2) & 3)) * 8, (seq >> 2) & 1);
        uint32_t rel = 0;
        auto pv_step = [&](int t, bool last) {
          if (__any_sync(0xffffffffu, (ua0 != 0x3f800000u) || (ua1 != 0x3f800000u))) {
            if (ua0 == 0xbf800000u) {
              __syncwarp();
              if (lane == 0) {
                mbar_expect_tx(pfull + pstage * 8, PMSG_W);
                mbar_arrive_remote(pempty_r + pstage * 8);
              }
              if (++pstage == PST) { pstage = 0; pphase ^= 1; }
              mbar_wait(pfull + pstage * 8, pphase);
              asm volatile("ld.shared.v2.b32 {%0, %1}, [%2];" : "=r"(ua0), "=r"(ua1) : "r"(mstat + pstage * PMSG_W) : "memory");
            }
            const float a0 = __uint_as_float(ua0), a1 = __uint_as_float(ua1);
#pragma unroll
            for (int j = 0; j < 32; j++) {
              o[4 * j] *= a0; o[4 * j + 1] *= a0; o[4 * j + 2] *= a1; o[4 * j + 3] *= a1;
            }
          }
          uint32_t p[16];
          const uint32_t src = mbox + pstage * PMSG_W;
#pragma unroll
          for (int j = 0; j < 3; j++) lds_v4(src + j * 512, p[4 * j], p[4 * j + 1], p[4 * j + 2], p[4 * j + 3]);
          const uint64_t db = make_desc(sbase + ((seq + 2) & 3) * SLOT, 8192, 1024);
          token_wait(wg);
          wg_fence();
          wgmma_n256_rs(o, p[0], p[1], p[2], p[3], db, t != 0);
          wg_commit();
          wgmma_n256_rs(o, p[4], p[5], p[6], p[7], db + 128, 1);
          wgmma_n256_rs(o, p[8], p[9], p[10], p[11], db + 256, 1);
          wg_commit();
          wg_wait<1>();
          lds_v4(src + 3 * 512, p[12], p[13], p[14], p[15]);
          wg_fence();
          wgmma_n256_rs(o, p[12], p[13], p[14], p[15], db + 384, 1);
          wg_commit();
          token_pass(wg);
          if (!last) {
            if (lane == 0) {
              mbar_expect_tx(pfull + pstage * 8, PMSG_W);
              mbar_arrive_remote(pempty_r + pstage * 8);
            }
            if (++pstage == PST) { pstage = 0; pphase ^= 1; }
          }
          if (rel == 11) issue_ring(m, seq - 1 + NS_O, sbase, b0, h, 1);
          seq++;
          if (!last) {
            mbar_wait(pfull + pstage * 8, pphase);
            asm volatile("ld.shared.v2.b32 {%0, %1}, [%2];" : "=r"(ua0), "=r"(ua1) : "r"(mstat + pstage * PMSG_W) : "memory");
            mbar_wait(bars + (BAR_VF + ((seq + 2) & 3)) * 8, (seq >> 2) & 1);
          }
          wg_wait<0>();
          fence_regs(o);
          rel = release_slot(bars + (BAR_VREL + ((seq + 1) & 3)) * 8, lane);
        };
#pragma unroll 1
        for (int t = 0; t < NKT - 1; t++) pv_step(t, false);
        pv_step(NKT - 1, true);
        uint32_t ui0, ui1;
        asm volatile("ld.shared.v2.b32 {%0, %1}, [%2];" : "=r"(ui0), "=r"(ui1) : "r"(mstat + pstage * PMSG_W + 8) : "memory");
        if (rel == 11) issue_ring(m, seq - 1 + NS_O, sbase, b0, h, 1);
        const float i0 = __uint_as_float(ui0), i1 = __uint_as_float(ui1);
#pragma unroll
        for (int j = 31; j >= 0; j--) {
          of[2 * j + 1] = pack_bf16_v(o[4 * j + 2] * i1, o[4 * j + 3] * i1);
          of[2 * j] = pack_bf16_v(o[4 * j] * i0, o[4 * j + 1] * i0);
        }
        __syncwarp();
        if (lane == 0) {
          mbar_expect_tx(pfull + pstage * 8, PMSG_W);
          mbar_arrive_remote(pempty_r + pstage * 8);
        }
        if (++pstage == PST) { pstage = 0; pphase ^= 1; }
      }
      if (it == 0) {
        mbar_wait(bars + BAR_XFREE * 8, 1);
#pragma unroll
        for (int j = 0; j < 16; j++) st_async_v4(xbuf_r + j * 512, of[4 * j], of[4 * j + 1], of[4 * j + 2], of[4 * j + 3], xf_r);
      } else {
        oproj(of);
      }
    }
  }
  __threadfence();
  __syncwarp();
  if (lane == 0) atomicAdd(g_cnt + rank, 1u);
  {
    uint4 va[NH];
    const int u = rank * 768 + cl * 12 + warp;
    wait_all(tid, 0);
    if (u < 4 * SLICES_PER_B) {
      slice_load(u, lane, va);
      slice_store(u, lane, va, out);
    }
    wait_all(tid, 1);
    if (u < 4 * SLICES_PER_B) {
      slice_load(4 * SLICES_PER_B + u, lane, va);
      slice_store(4 * SLICES_PER_B + u, lane, va, out);
    }
    __syncwarp();
    if (lane == 0) {
      if (atomicAdd(g_done, 1u) == 128 * 12 - 1) { g_cnt[0] = 0; g_cnt[1] = 0; g_done[0] = 0; }
    }
  }
}

typedef CUresult (*PFN_encodeTiled)(CUtensorMap*, CUtensorMapDataType, cuuint32_t, void*, const cuuint64_t*, const cuuint64_t*,
                                    const cuuint32_t*, const cuuint32_t*, CUtensorMapInterleave, CUtensorMapSwizzle,
                                    CUtensorMapL2promotion, CUtensorMapFloatOOBfill);

void encode(PFN_encodeTiled fn, CUtensorMap* m, int rank, const void* ptr, const cuuint64_t* dims, const cuuint64_t* strides,
            const cuuint32_t* box) {
  cuuint32_t es[3] = {1, 1, 1};
  fn(m, CU_TENSOR_MAP_DATA_TYPE_BFLOAT16, (cuuint32_t)rank, const_cast<void*>(ptr), dims, strides, box, es,
     CU_TENSOR_MAP_INTERLEAVE_NONE, CU_TENSOR_MAP_SWIZZLE_128B, CU_TENSOR_MAP_L2_PROMOTION_L2_256B,
     CU_TENSOR_MAP_FLOAT_OOB_FILL_NONE);
}

}

extern "C" void kernel_launch(void* const* d_in, const int* in_sizes, int n_in, void* d_out, int out_size) {
  const void* x = d_in[0];
  const void* kc = d_in[1];
  const void* vc = d_in[2];
  const void* wq = d_in[3];
  const void* wo = d_in[4];

  static PFN_encodeTiled fn = nullptr;
  if (!fn) {
    void* p = nullptr;
    cudaDriverEntryPointQueryResult qr;
    cudaGetDriverEntryPoint("cuTensorMapEncodeTiled", &p, cudaEnableDefault, &qr);
    fn = (PFN_encodeTiled)p;
    cudaFuncSetAttribute(mha_kernel, cudaFuncAttributeMaxDynamicSharedMemorySize, SMEM_BYTES);
  }
  CUtensorMap tm_x, tm_wq, tm_k, tm_v, tm_wo;
  {
    cuuint64_t dims[2] = {DM, (cuuint64_t)NB * SQ};
    cuuint64_t str[1] = {DM * 2};
    cuuint32_t box[2] = {64, SQ};
    encode(fn, &tm_x, 2, x, dims, str, box);
  }
  {
    cuuint64_t dims[3] = {64, DM, (cuuint64_t)NH * DH / 64};
    cuuint64_t str[2] = {(cuuint64_t)NH * DH * 2, 128};
    cuuint32_t box[3] = {64, 64, 4};
    encode(fn, &tm_wq, 3, wq, dims, str, box);
  }
  {
    cuuint64_t dims[3] = {64, (cuuint64_t)NB * NH * SK, 4};
    cuuint64_t str[2] = {DH * 2, 128};
    cuuint32_t box[3] = {64, 64, 4};
    encode(fn, &tm_k, 3, kc, dims, str, box);
    encode(fn, &tm_v, 3, vc, dims, str, box);
  }
  {
    cuuint64_t dims[2] = {DM, (cuuint64_t)NH * DH};
    cuuint64_t str[1] = {DM * 2};
    cuuint32_t box[2] = {64, DH};
    encode(fn, &tm_wo, 2, wo, dims, str, box);
  }
  mha_kernel<<<128, 384, SMEM_BYTES>>>(tm_x, tm_wq, tm_k, tm_v, tm_wo, (const __nv_bfloat16*)kc, (const __nv_bfloat16*)vc,
                                       (const __nv_bfloat16*)x, (const __nv_bfloat16*)wq, (__nv_bfloat16*)d_out);
}
```

```cpp
#include <cuda_runtime.h>
#include <cuda_bf16.h>
#include <cuda.h>
#include <stdint.h>
#include <type_traits>

namespace {

constexpr int NB = 8, SQ = 192, DM = 448, NH = 16, SK = 1024, DH = 256;
constexpr int SLOT = 32768;
constexpr int NS_O = 4;
constexpr int PST = 3;
constexpr int PMSG_W = 2176;
constexpr int NKT = SK / 64;
constexpr int NKC = DM / 64;
constexpr int PF_K0 = 1, PF_HEAD = 3;

constexpr int OFF_MBOX = NS_O * SLOT;
constexpr int OFF_XBUF = 2 * 2 * SLOT;
constexpr int OFF_BAR = OFF_XBUF + 3 * SLOT;
static_assert(OFF_BAR >= OFF_MBOX + 12 * PST * PMSG_W, "smem layout");
constexpr int BAR_SF = 0;
constexpr int BAR_VF = 4;
constexpr int BAR_SREL = 8;
constexpr int BAR_VREL = 12;
constexpr int BAR_XFREE = 16;
constexpr int BAR_XF = 17;
constexpr int BAR_P = 20;
constexpr int NBARS = BAR_P + 12 * PST;
constexpr int SMEM_BYTES = OFF_BAR + NBARS * 8 + 1024;

constexpr int SLICES_PER_B = NKC * 3 * 4 * 4;

__device__ uint4 g_part[(size_t)NB * NH * NKC * 3 * 4 * 128];
__device__ unsigned int g_cnt[2];
__device__ unsigned int g_done[1];

__device__ __forceinline__ uint32_t smem_u32(const void* p) { return (uint32_t)__cvta_generic_to_shared(p); }

__device__ __forceinline__ void mbar_init(uint32_t bar, uint32_t cnt) {
  asm volatile("mbarrier.init.shared::cta.b64 [%0], %1;" ::"r"(bar), "r"(cnt) : "memory");
}
__device__ __forceinline__ void mbar_expect_tx(uint32_t bar, uint32_t bytes) {
  asm volatile("mbarrier.arrive.expect_tx.shared::cta.b64 _, [%0], %1;" ::"r"(bar), "r"(bytes) : "memory");
}
__device__ __forceinline__ void mbar_arrive_remote(uint32_t rbar) {
  asm volatile("mbarrier.arrive.shared::cluster.b64 _, [%0];" ::"r"(rbar) : "memory");
}
constexpr uint32_t SPIN_LIMIT = 1u << 22;
__device__ __forceinline__ void mbar_wait(uint32_t bar, uint32_t parity) {
  asm volatile(
      "{\n.reg .pred p, q;\n.reg .u32 n;\n"
      "mbarrier.try_wait.parity.shared::cta.b64 p, [%0], %1;\n"
      "@p bra.uni DONE_%=;\n"
      "mov.u32 n, 0;\n"
      "LOOP_%=:\n"
      "mbarrier.try_wait.parity.shared::cta.b64 p, [%0], %1;\n"
      "@p bra.uni DONE_%=;\n"
      "add.u32 n, n, 1;\n"
      "setp.lt.u32 q, n, 4194304;\n"
      "@q bra.uni LOOP_%=;\n"
      "trap;\n"
      "DONE_%=:\n}"
      ::"r"(bar), "r"(parity) : "memory");
}
__device__ __forceinline__ uint32_t mapa(uint32_t addr, uint32_t rank) {
  uint32_t r;
  asm volatile("mapa.shared::cluster.u32 %0, %1, %2;" : "=r"(r) : "r"(addr), "r"(rank));
  return r;
}
__device__ __forceinline__ void tma_2d(uint32_t dst, const CUtensorMap* tm, int c0, int c1, uint32_t bar) {
  asm volatile("cp.async.bulk.tensor.2d.shared::cluster.global.mbarrier::complete_tx::bytes [%0], [%1, {%3, %4}], [%2];"
               ::"r"(dst), "l"(tm), "r"(bar), "r"(c0), "r"(c1) : "memory");
}
__device__ __forceinline__ void tma_3d(uint32_t dst, const CUtensorMap* tm, int c0, int c1, int c2, uint32_t bar) {
  asm volatile("cp.async.bulk.tensor.3d.shared::cluster.global.mbarrier::complete_tx::bytes [%0], [%1, {%3, %4, %5}], [%2];"
               ::"r"(dst), "l"(tm), "r"(bar), "r"(c0), "r"(c1), "r"(c2) : "memory");
}
__device__ __forceinline__ void tma_3d_ef(uint32_t dst, const CUtensorMap* tm, int c0, int c1, int c2, uint32_t bar) {
  asm volatile("{\n.reg .b64 pol;\ncreatepolicy.fractional.L2::evict_first.b64 pol, 1.0;\n"
               "cp.async.bulk.tensor.3d.shared::cluster.global.mbarrier::complete_tx::bytes.L2::cache_hint [%0], [%1, {%3, %4, %5}], [%2], pol;\n}"
               ::"r"(dst), "l"(tm), "r"(bar), "r"(c0), "r"(c1), "r"(c2) : "memory");
}
__device__ __forceinline__ void l2_prefetch(const void* p, uint32_t bytes) {
  asm volatile("cp.async.bulk.prefetch.L2.global [%0], %1;" ::"l"(p), "r"(bytes) : "memory");
}
__device__ __forceinline__ void st_async_v4(uint32_t raddr, uint32_t a, uint32_t b, uint32_t c, uint32_t d, uint32_t rbar) {
  asm volatile("st.async.weak.shared::cluster.mbarrier::complete_tx::bytes.v4.b32 [%0], {%1, %2, %3, %4}, [%5];"
               ::"r"(raddr), "r"(a), "r"(b), "r"(c), "r"(d), "r"(rbar) : "memory");
}
__device__ __forceinline__ void lds_v4(uint32_t addr, uint32_t& a, uint32_t& b, uint32_t& c, uint32_t& d) {
  asm volatile("ld.shared.v4.b32 {%0, %1, %2, %3}, [%4];" : "=r"(a), "=r"(b), "=r"(c), "=r"(d) : "r"(addr) : "memory");
}
__device__ __forceinline__ uint32_t pack_bf16(float lo, float hi) {
  uint32_t r;
  asm("cvt.rn.bf16x2.f32 %0, %1, %2;" : "=r"(r) : "f"(hi), "f"(lo));
  return r;
}
__device__ __forceinline__ uint32_t pack_bf16_v(float lo, float hi) {
  uint32_t r;
  asm volatile("cvt.rn.bf16x2.f32 %0, %1, %2;" : "=r"(r) : "f"(hi), "f"(lo));
  return r;
}
__device__ __forceinline__ float ex2v(float x) {
  float r;
  asm volatile("ex2.approx.ftz.f32 %0, %1;" : "=f"(r) : "f"(x));
  return r;
}
__device__ __forceinline__ float ex2(float x) {
  float r;
  asm("ex2.approx.ftz.f32 %0, %1;" : "=f"(r) : "f"(x));
  return r;
}

__device__ __forceinline__ uint64_t make_desc(uint32_t addr, uint32_t lbo, uint32_t sbo) {
  return (uint64_t)((addr & 0x3FFFF) >> 4) | ((uint64_t)(lbo >> 4) << 16) | ((uint64_t)(sbo >> 4) << 32) | (1ull << 62);
}
__device__ __forceinline__ void wg_fence() { asm volatile("wgmma.fence.sync.aligned;" ::: "memory"); }
__device__ __forceinline__ void wg_commit() { asm volatile("wgmma.commit_group.sync.aligned;" ::: "memory"); }
template <int N> __device__ __forceinline__ void wg_wait() { asm volatile("wgmma.wait_group.sync.aligned %0;" ::"n"(N) : "memory"); }
template <int N> __device__ __forceinline__ void fence_regs(float (&r)[N]) {
#pragma unroll
  for (int i = 0; i < N; i++) asm volatile("" : "+f"(r[i])::"memory");
}

#define F8(a, o) "+f"(a[o + 0]), "+f"(a[o + 1]), "+f"(a[o + 2]), "+f"(a[o + 3]), "+f"(a[o + 4]), "+f"(a[o + 5]), "+f"(a[o + 6]), "+f"(a[o + 7])
#define F32(a, o) F8(a, o), F8(a, o + 8), F8(a, o + 16), F8(a, o + 24)
#define F128(a) F32(a, 0), F32(a, 32), F32(a, 64), F32(a, 96)
#define D32 "{%0, %1, %2, %3, %4, %5, %6, %7, %8, %9, %10, %11, %12, %13, %14, %15, %16, %17, %18, %19, %20, %21, %22, %23, %24, %25, %26, %27, %28, %29, %30, %31}"
#define D128 "{%0, %1, %2, %3, %4, %5, %6, %7, %8, %9, %10, %11, %12, %13, %14, %15, %16, %17, %18, %19, %20, %21, %22, %23, %24, %25, %26, %27, %28, %29, %30, %31, " \
  "%32, %33, %34, %35, %36, %37, %38, %39, %40, %41, %42, %43, %44, %45, %46, %47, %48, %49, %50, %51, %52, %53, %54, %55, %56, %57, %58, %59, %60, %61, %62, %63, " \
  "%64, %65, %66, %67, %68, %69, %70, %71, %72, %73, %74, %75, %76, %77, %78, %79, %80, %81, %82, %83, %84, %85, %86, %87, %88, %89, %90, %91, %92, %93, %94, %95, " \
  "%96, %97, %98, %99, %100, %101, %102, %103, %104, %105, %106, %107, %108, %109, %110, %111, %112, %113, %114, %115, %116, %117, %118, %119, %120, %121, %122, %123, %124, %125, %126, %127}"

__device__ __forceinline__ void wgmma_n256_ss(float (&d)[128], uint64_t da, uint64_t db, int scale_d) {
  asm volatile("{\n.reg .pred p;\nsetp.ne.b32 p, %130, 0;\n"
               "wgmma.mma_async.sync.aligned.m64n256k16.f32.bf16.bf16 " D128 ", %128, %129, p, 1, 1, 0, 1;\n}"
               : F128(d) : "l"(da), "l"(db), "r"(scale_d));
}
__device__ __forceinline__ void wgmma_n256_rs(float (&d)[128], uint32_t a0, uint32_t a1, uint32_t a2, uint32_t a3, uint64_t db, int scale_d) {
  asm volatile("{\n.reg .pred p;\nsetp.ne.b32 p, %133, 0;\n"
               "wgmma.mma_async.sync.aligned.m64n256k16.f32.bf16.bf16 " D128 ", {%128, %129, %130, %131}, %132, p, 1, 1, 1;\n}"
               : F128(d) : "r"(a0), "r"(a1), "r"(a2), "r"(a3), "l"(db), "r"(scale_d));
}
template <int TB>
__device__ __forceinline__ void wgmma_n64_rs(float (&d)[32], uint32_t a0, uint32_t a1, uint32_t a2, uint32_t a3, uint64_t db, int scale_d) {
  asm volatile("{\n.reg .pred p;\nsetp.ne.b32 p, %37, 0;\n"
               "wgmma.mma_async.sync.aligned.m64n64k16.f32.bf16.bf16 " D32 ", {%32, %33, %34, %35}, %36, p, 1, 1, %38;\n}"
               : F32(d, 0) : "r"(a0), "r"(a1), "r"(a2), "r"(a3), "l"(db), "r"(scale_d), "n"(TB));
}

__device__ __forceinline__ void token_wait(int wg) { asm volatile("bar.sync %0, 256;" ::"r"(wg + 1) : "memory"); }
__device__ __forceinline__ void token_pass(int wg) { asm volatile("bar.arrive %0, 256;" ::"r"(wg == 2 ? 1 : wg + 2) : "memory"); }

__device__ __forceinline__ void slice_load(int s, int lane, uint4 (&v)[NH]) {
  const int b = s / SLICES_PER_B, r = s % SLICES_PER_B;
  const uint4* src = g_part + ((size_t)b * NH * NKC * 3 * 4 * 128 + (size_t)r * 32 + lane);
  constexpr size_t HSTRIDE = (size_t)NKC * 3 * 4 * 128;
#pragma unroll
  for (int i = 0; i < NH; i++) v[i] = __ldcg(src + (size_t)i * HSTRIDE);
}
__device__ __forceinline__ void slice_store(int s, int lane, const uint4 (&v)[NH], __nv_bfloat16* out) {
  const int b = s / SLICES_PER_B, r = s % SLICES_PER_B;
  const int warp = r & 3, j = (r >> 2) & 3, cw = r >> 4;
  const int w = cw % 3, c = cw / 3;
  float acc[8];
#pragma unroll
  for (int i = 0; i < 8; i++) acc[i] = 0.f;
#pragma unroll
  for (int i = 0; i < NH; i++) {
    acc[0] += __uint_as_float(v[i].x << 16); acc[1] += __uint_as_float(v[i].x & 0xffff0000u);
    acc[2] += __uint_as_float(v[i].y << 16); acc[3] += __uint_as_float(v[i].y & 0xffff0000u);
    acc[4] += __uint_as_float(v[i].z << 16); acc[5] += __uint_as_float(v[i].z & 0xffff0000u);
    acc[6] += __uint_as_float(v[i].w << 16); acc[7] += __uint_as_float(v[i].w & 0xffff0000u);
  }
  const int g = lane >> 2, q = lane & 3;
  const int row = w * 64 + warp * 16 + g;
  const int col = c * 64 + j * 16 + 2 * q;
  uint32_t* o = reinterpret_cast<uint32_t*>(out + ((size_t)(b * SQ + row) * DM + col));
  o[0] = pack_bf16(acc[0], acc[1]);
  o[8 * DM / 2] = pack_bf16(acc[2], acc[3]);
  o[4] = pack_bf16(acc[4], acc[5]);
  o[8 * DM / 2 + 4] = pack_bf16(acc[6], acc[7]);
}

__device__ __forceinline__ void wait_all(int tid, int idx) {
  if (tid == 0) {
    uint32_t n = 0;
    while (true) {
      unsigned int v;
      asm volatile("ld.acquire.gpu.global.u32 %0, [%1];" : "=r"(v) : "l"(g_cnt + idx) : "memory");
      if (v >= 64u * 12u) break;
      __nanosleep(20);
      if (++n > SPIN_LIMIT) __trap();
    }
  }
  asm volatile("bar.sync 4, 384;" ::: "memory");
}

struct Maps {
  const CUtensorMap *x, *wq, *k, *v, *wo;
  const char *kptr, *vptr, *xptr;
};
__device__ __forceinline__ void load_chunk(const Maps& m, int c, uint32_t sbase, int b, int h) {
  const uint32_t stage = c % 3;
  const uint32_t dst = sbase + stage * (2 * SLOT);
  const uint32_t bar = sbase + OFF_BAR + (BAR_SF + stage) * 8;
  mbar_expect_tx(bar, SLOT + SQ * 128);
  tma_2d(dst, m.x, c * 64, b * SQ, bar);
  tma_3d(dst + SLOT, m.wq, 0, c * 64, h * 4, bar);
}
__device__ __forceinline__ void issue_ring(const Maps& m, int n, uint32_t sbase, int b0, int h, uint32_t rank) {
  if (n >= 2 * NKT + NKC) return;
  const uint32_t slot = (n + 2) & 3;
  const uint32_t dst = sbase + slot * SLOT;
  const uint32_t bar = sbase + OFF_BAR + (BAR_VF + slot) * 8;
  mbar_expect_tx(bar, SLOT);
  if (n < 2 * NKT) tma_3d_ef(dst, rank ? m.v : m.k, 0, ((b0 + 4 * (n >> 4)) * NH + h) * SK + (n & 15) * 64, 0, bar);
  else tma_2d(dst, m.wo, (n - 2 * NKT) * 64, h * DH, bar);
}
__device__ __forceinline__ void store_chunk(uint4* dst, const float (&a)[32]) {
#pragma unroll
  for (int j = 0; j < 4; j++) {
    uint4 w;
    w.x = pack_bf16(a[8 * j], a[8 * j + 1]);
    w.y = pack_bf16(a[8 * j + 2], a[8 * j + 3]);
    w.z = pack_bf16(a[8 * j + 4], a[8 * j + 5]);
    w.w = pack_bf16(a[8 * j + 6], a[8 * j + 7]);
    dst[j * 128] = w;
  }
}
__device__ __forceinline__ void pf_tile(const Maps& m, int b0, int h, int it, int kv, int j) {
  if (j < NKT) l2_prefetch((kv ? m.vptr : m.kptr) + ((size_t)((b0 + 4 * it) * NH + h) * NKT + j) * SLOT, SLOT);
}

__device__ __forceinline__ uint32_t release_slot(uint32_t cnt_addr, int lane) {
  uint32_t old = 0;
  if (lane == 0) asm volatile("atom.relaxed.cta.shared.inc.u32 %0, [%1], 11;" : "=r"(old) : "r"(cnt_addr) : "memory");
  return old;
}

__global__ void __cluster_dims__(2, 1, 1) __launch_bounds__(384, 1)
mha_kernel(const __grid_constant__ CUtensorMap tm_x, const __grid_constant__ CUtensorMap tm_wq,
           const __grid_constant__ CUtensorMap tm_k, const __grid_constant__ CUtensorMap tm_v,
           const __grid_constant__ CUtensorMap tm_wo, const __nv_bfloat16* __restrict__ kptr,
           const __nv_bfloat16* __restrict__ vptr, const __nv_bfloat16* __restrict__ xptr,
           const __nv_bfloat16* __restrict__ wqptr, __nv_bfloat16* __restrict__ out) {
  extern __shared__ uint8_t smem_raw[];
  const uint32_t sbase = (smem_u32(smem_raw) + 1023u) & ~1023u;
  const uint32_t bars = sbase + OFF_BAR;
  const int tid = threadIdx.x;
  const int warp = __shfl_sync(0xffffffffu, tid >> 5, 0), lane = tid & 31;
  const int wg = warp >> 2;
  uint32_t rank;
  asm volatile("mov.u32 %0, %%cluster_ctarank;" : "=r"(rank));
  const int cl = blockIdx.x >> 1;
  const int h = cl & 15;
  const int b0 = cl >> 4;

  Maps m{&tm_x, &tm_wq, &tm_k, &tm_v, &tm_wo, reinterpret_cast<const char*>(kptr), reinterpret_cast<const char*>(vptr),
         reinterpret_cast<const char*>(xptr)};
  if (tid == 0) {
    for (int i = 0; i < 8; i++) {
      mbar_init(bars + i * 8, 1);
      asm volatile("st.shared.u32 [%0], 0;" ::"r"(bars + (BAR_SREL + i) * 8) : "memory");
    }
    asm volatile("fence.mbarrier_init.release.cluster;" ::: "memory");
    asm volatile("fence.proxy.async.shared::cta;" ::: "memory");
    for (int i = 0; i < 3; i++) load_chunk(m, i, sbase, b0 + 4 * rank, h);
  } else if (tid == 32) {
    mbar_init(bars + BAR_XFREE * 8, 1);
    mbar_init(bars + BAR_XF * 8, 1);
    for (int i = 0; i < 12 * PST; i++) mbar_init(bars + (BAR_P + i) * 8, 1);
    if (rank == 1) {
      for (int i = 0; i < 12 * PST; i++) mbar_expect_tx(bars + (BAR_P + i) * 8, PMSG_W);
    } else {
      mbar_expect_tx(bars + BAR_XF * 8, 3 * SLOT);
    }
    asm volatile("fence.mbarrier_init.release.cluster;" ::: "memory");
  }
  __syncthreads();
  asm volatile("barrier.cluster.arrive.relaxed.aligned;\nbarrier.cluster.wait.aligned;" ::: "memory");

  uint32_t sph = 0;
  uint32_t q[64];
  {
    float acc[128];
#pragma unroll
    for (int i = 0; i < 128; i++) acc[i] = 0.f;
    auto after_chunk = [&](int c) {
      if (c < 4) load_chunk(m, c + 3, sbase, b0 + 4 * rank, h);
      else if (c == 5) {
        if (rank == 0) mbar_arrive_remote(mapa(bars + BAR_XFREE * 8, 1));
      } else {
        issue_ring(m, c - 4, sbase, b0, h, rank);
        issue_ring(m, c - 3, sbase, b0, h, rank);
      }
    };
    uint32_t st = 0, prev = 0;
#pragma unroll 1
    for (int kc = 0; kc < NKC; kc++) {
      mbar_wait(bars + (BAR_SF + st) * 8, (sph >> st) & 1);
      sph ^= 1u << st;
      const uint64_t da = make_desc(sbase + st * (2 * SLOT) + wg * 8192, 16, 1024);
      const uint64_t db = make_desc(sbase + st * (2 * SLOT) + SLOT, 8192, 1024);
      wg_fence();
#pragma unroll
      for (int ks = 0; ks < 4; ks++) wgmma_n256_ss(acc, da + ks * 2, db + ks * 128, (kc | ks) != 0);
      wg_commit();
      if (kc == 0 && tid == 320) {
        l2_prefetch(reinterpret_cast<const char*>(wqptr) + (size_t)192 * NH * DH * 2 + (size_t)blockIdx.x * (256 * NH * DH * 2 / 128), 256 * NH * DH * 2 / 128);
        l2_prefetch(m.xptr + (size_t)blockIdx.x * (NB * SQ * DM * 2 / 128), NB * SQ * DM * 2 / 128);
      }
      if (rank == 0 && (tid & 127) == 64 && wg < 2 && kc >= PF_K0 && kc < PF_K0 + PF_HEAD) pf_tile(m, b0, h, 0, wg, kc - PF_K0);
      if (kc > 0) {
        wg_wait<1>();
        if (release_slot(bars + (BAR_SREL + prev) * 8, lane) == 11) after_chunk(kc - 1);
      }
      prev = st;
      st = st == 2 ? 0 : st + 1;
    }
    wg_wait<0>();
    fence_regs(acc);
    if (release_slot(bars + (BAR_SREL + prev) * 8, lane) == 11) after_chunk(NKC - 1);
#pragma unroll
    for (int i = 63; i >= 0; i--) q[i] = pack_bf16_v(acc[2 * i], acc[2 * i + 1]);
  }

  int seq = 0;
  auto oproj = [&](uint32_t (&of)[64]) {
    uint32_t tid2;
    asm volatile("mov.u32 %0, %%tid.x;" : "=r"(tid2));
    uint4* dst = g_part + ((size_t)((b0 + 4 * rank) * NH + h) * NKC * 3 * 4 * 128 + (size_t)wg * 4 * 128 + (tid2 & 127));
    float acc[2][32];
#pragma unroll
    for (int i = 0; i < 32; i++) { acc[0][i] = 0.f; acc[1][i] = 0.f; }
#pragma unroll
    for (int c = 0; c <= NKC; c++) {
      constexpr int n0 = 2 * NKT;
      if (c < NKC) {
        const uint32_t slot = (n0 + c + 2) & 3;
        mbar_wait(bars + (BAR_VF + slot) * 8, ((n0 + c) >> 2) & 1);
        uint32_t sb2;
        asm volatile("mov.u32 %0, %1;" : "=r"(sb2) : "r"(sbase));
        const uint64_t db = make_desc(sb2 + slot * SLOT, 8192, 1024);
        wg_fence();
#pragma unroll
        for (int ks = 0; ks < 16; ks++)
          wgmma_n64_rs<1>(acc[c & 1], of[4 * ks], of[4 * ks + 1], of[4 * ks + 2], of[4 * ks + 3], db + ks * 128, ks != 0);
        wg_commit();
      }
      if (c > 0) {
        if (c < NKC) wg_wait<1>(); else wg_wait<0>();
        float(&a)[32] = acc[(c - 1) & 1];
        fence_regs(a);
        uint32_t rel = 0;
        if (c - 1 + NS_O < NKC) rel = release_slot(bars + (BAR_VREL + ((n0 + c + 1) & 3)) * 8, lane);
        store_chunk(dst + (size_t)(c - 1) * (3 * 4 * 128), a);
        if (rel == 11) issue_ring(m, n0 + c - 1 + NS_O, sbase, b0, h, rank);
      }
    }
  };
  if (rank == 0) {
    uint32_t pstage = 0, pphase = 0;
    const uint32_t mbox_r = mapa(sbase + OFF_MBOX + warp * (PST * PMSG_W) + lane * 16, 1);
    const uint32_t pfull_r = mapa(bars + (BAR_P + warp * PST) * 8, 1);
    const uint32_t pempty = bars + (BAR_P + warp * PST) * 8;
    const uint32_t xbuf = sbase + OFF_XBUF + warp * 8192 + lane * 16;
    const float cs = 0.0625f * 1.4426950408889634f;
#pragma unroll 1
    for (int it = 0; it < 2; it++) {
      if (it == 1) {
        mbar_wait(bars + BAR_XF * 8, 0);
#pragma unroll
        for (int j = 0; j < 16; j++) lds_v4(xbuf + j * 512, q[4 * j], q[4 * j + 1], q[4 * j + 2], q[4 * j + 3]);
      }
      float n0 = INFINITY, n1 = INFINITY, l0 = 0.f, l1 = 0.f;
      float sA[32], sB[32];
#pragma unroll
      for (int i = 0; i < 32; i++) { sA[i] = 0.f; sB[i] = 0.f; }
      float a0 = 1.f, a1 = 1.f;
      auto new_ref = [&](float (&s)[32]) {
        float mx0 = fmaxf(s[0], s[1]), mx1 = fmaxf(s[2], s[3]);
#pragma unroll
        for (int j = 1; j < 8; j++) {
          mx0 = fmaxf(mx0, fmaxf(s[4 * j], s[4 * j + 1]));
          mx1 = fmaxf(mx1, fmaxf(s[4 * j + 2], s[4 * j + 3]));
        }
        mx0 = fmaxf(mx0, __shfl_xor_sync(0xffffffffu, mx0, 1));
        mx1 = fmaxf(mx1, __shfl_xor_sync(0xffffffffu, mx1, 1));
        mx0 = fmaxf(mx0, __shfl_xor_sync(0xffffffffu, mx0, 2));
        mx1 = fmaxf(mx1, __shfl_xor_sync(0xffffffffu, mx1, 2));
        const float n0n = fminf(n0, -mx0 * cs), n1n = fminf(n1, -mx1 * cs);
        a0 = ex2(n0n - n0); a1 = ex2(n1n - n1);
        n0 = n0n; n1 = n1n;
        l0 *= a0; l1 *= a1;
      };
      auto step = [&](float (&s)[32], float (&sn)[32], uint64_t db, auto mma_tag, bool fresh_ref, bool last) {
        constexpr bool MMA = decltype(mma_tag)::value;
        mbar_wait(pempty + pstage * 8, pphase);
        uint32_t dst = mbox_r + pstage * PMSG_W;
        uint32_t rb = pfull_r + pstage * 8;
        float s0 = 0.f, s1 = 0.f;
        uint32_t p[4];
        if (MMA) wg_fence();
#pragma unroll
        for (int ks = 0; ks < 16; ks++) {
          if (MMA)
            wgmma_n64_rs<0>(sn, q[4 * ks], q[4 * ks + 1], q[4 * ks + 2], q[4 * ks + 3], db + (ks >> 2) * 512 + (ks & 3) * 2, ks != 0);
          const float nn = (ks & 1) ? n1 : n0;
          const float e0 = ex2v(fmaf(s[2 * ks], cs, nn)), e1 = ex2v(fmaf(s[2 * ks + 1], cs, nn));
          if (ks & 1) s1 += e0 + e1; else s0 += e0 + e1;
          p[ks & 3] = pack_bf16(e0, e1);
          if ((ks & 3) == 3) st_async_v4(dst + (ks >> 2) * 512, p[0], p[1], p[2], p[3], rb);
        }
        if (MMA) wg_commit();
        if (!fresh_ref && __any_sync(0xffffffffu, !(s0 <= 1048576.f) || !(s1 <= 1048576.f))) {
          if ((lane & 3) == 0) st_async_v4(dst + 2048 - lane * 12, 0xbf800000u, 0u, 0u, 0u, rb);
          if (++pstage == PST) { pstage = 0; pphase ^= 1; }
          new_ref(s);
          mbar_wait(pempty + pstage * 8, pphase);
          dst = mbox_r + pstage * PMSG_W;
          rb = pfull_r + pstage * 8;
          s0 = 0.f; s1 = 0.f;
#pragma unroll
          for (int ks = 0; ks < 16; ks++) {
            const float nn = (ks & 1) ? n1 : n0;
            const float e0 = ex2(fmaf(s[2 * ks], cs, nn)), e1 = ex2(fmaf(s[2 * ks + 1], cs, nn));
            if (ks & 1) s1 += e0 + e1; else s0 += e0 + e1;
            p[ks & 3] = pack_bf16(e0, e1);
            if ((ks & 3) == 3) st_async_v4(dst + (ks >> 2) * 512, p[0], p[1], p[2], p[3], rb);
          }
        }
        l0 += s0; l1 += s1;
        float i0 = 0.f, i1 = 0.f;
        if (last) {
          float t0 = l0 + __shfl_xor_sync(0xffffffffu, l0, 1);
          float t1 = l1 + __shfl_xor_sync(0xffffffffu, l1, 1);
          t0 += __shfl_xor_sync(0xffffffffu, t0, 2);
          t1 += __shfl_xor_sync(0xffffffffu, t1, 2);
          i0 = __frcp_rn(t0); i1 = __frcp_rn(t1);
        }
        if ((lane & 3) == 0)
          st_async_v4(dst + 2048 - lane * 12, __float_as_uint(a0), __float_as_uint(a1), __float_as_uint(i0), __float_as_uint(i1), rb);
        a0 = 1.f; a1 = 1.f;
        if (++pstage == PST) { pstage = 0; pphase ^= 1; }
      };
      auto kdesc = [&]() {
        const uint32_t slot = (seq + 2) & 3;
        mbar_wait(bars + (BAR_VF + slot) * 8, (seq >> 2) & 1);
        return make_desc(sbase + slot * SLOT, 16, 1024);
      };
      auto kdone = [&]() {
        if (release_slot(bars + (BAR_VREL + ((seq + 2) & 3)) * 8, lane) == 11) issue_ring(m, seq + NS_O, sbase, b0, h, 0);
        __syncwarp();
        seq++;
      };
      {
        const uint64_t db = kdesc();
        wg_fence();
#pragma unroll
        for (int ks = 0; ks < 16; ks++)
          wgmma_n64_rs<0>(sA, q[4 * ks], q[4 * ks + 1], q[4 * ks + 2], q[4 * ks + 3], db + (ks >> 2) * 512 + (ks & 3) * 2, ks != 0);
        wg_commit();
        if (it == 1 && release_slot(bars + (BAR_SREL + 2) * 8, lane) == 11) {
          mbar_expect_tx(bars + BAR_XF * 8, 3 * SLOT);
          mbar_arrive_remote(mapa(bars + BAR_XFREE * 8, 1));
        }
        wg_wait<0>();
        fence_regs(sA);
        kdone();
        new_ref(sA);
      }
#pragma unroll 1
      for (int t = 0; t < NKT; t += 2) {
        step(sA, sB, kdesc(), std::true_type{}, t == 0, false);
        wg_wait<0>();
        fence_regs(sB);
        kdone();
        if (t + 2 < NKT) {
          step(sB, sA, kdesc(), std::true_type{}, false, false);
          wg_wait<0>();
          fence_regs(sA);
          kdone();
        } else {
          step(sB, sA, 0, std::false_type{}, false, true);
        }
      }
    }
    uint32_t of[64];
    mbar_wait(bars + BAR_XF * 8, 1);
#pragma unroll
    for (int j = 0; j < 16; j++) lds_v4(xbuf + j * 512, of[4 * j], of[4 * j + 1], of[4 * j + 2], of[4 * j + 3]);
    oproj(of);
  } else {
    uint32_t pstage = 0, pphase = 0;
    const uint32_t mbox = sbase + OFF_MBOX + warp * (PST * PMSG_W) + lane * 16;
    const uint32_t mstat = sbase + OFF_MBOX + warp * (PST * PMSG_W) + 2048 + (lane >> 2) * 16;
    const uint32_t pfull = bars + (BAR_P + warp * PST) * 8;
    const uint32_t pempty_r = mapa(bars + (BAR_P + warp * PST) * 8, 0);
    const uint32_t xbuf_r = mapa(sbase + OFF_XBUF + warp * 8192 + lane * 16, 0);
    const uint32_t xf_r = mapa(bars + BAR_XF * 8, 0);
    {
      asm volatile("bar.sync 4, 384;" ::: "memory");
      if (lane < PST) mbar_arrive_remote(pempty_r + lane * 8);
      __syncwarp();
      mbar_wait(bars + BAR_XFREE * 8, 0);
#pragma unroll
      for (int j = 0; j < 16; j++) st_async_v4(xbuf_r + j * 512, q[4 * j], q[4 * j + 1], q[4 * j + 2], q[4 * j + 3], xf_r);
      if (wg == 2) token_pass(2);
    }
#pragma unroll 1
    for (int it = 0; it < 2; it++) {
      uint32_t of[64];
      {
        float o[128];
#pragma unroll
        for (int i = 0; i < 128; i++) o[i] = 0.f;
        uint32_t ua0 = 0x3f800000u, ua1 = 0x3f800000u;
        mbar_wait(pfull + pstage * 8, pphase);
        mbar_wait(bars + (BAR_VF + ((seq + 2) & 3)) * 8, (seq >> 2) & 1);
        auto pv_step = [&](int t, bool last) {
          if (__any_sync(0xffffffffu, (ua0 != 0x3f800000u) || (ua1 != 0x3f800000u))) {
            if (ua0 == 0xbf800000u) {
              __syncwarp();
              if (lane == 0) {
                mbar_expect_tx(pfull + pstage * 8, PMSG_W);
                mbar_arrive_remote(pempty_r + pstage * 8);
              }
              if (++pstage == PST) { pstage = 0; pphase ^= 1; }
              mbar_wait(pfull + pstage * 8, pphase);
              asm volatile("ld.shared.v2.b32 {%0, %1}, [%2];" : "=r"(ua0), "=r"(ua1) : "r"(mstat + pstage * PMSG_W) : "memory");
            }
            const float a0 = __uint_as_float(ua0), a1 = __uint_as_float(ua1);
#pragma unroll
            for (int j = 0; j < 32; j++) {
              o[4 * j] *= a0; o[4 * j + 1] *= a0; o[4 * j + 2] *= a1; o[4 * j + 3] *= a1;
            }
          }
          uint32_t p[16];
          const uint32_t src = mbox + pstage * PMSG_W;
#pragma unroll
          for (int j = 0; j < 3; j++) lds_v4(src + j * 512, p[4 * j], p[4 * j + 1], p[4 * j + 2], p[4 * j + 3]);
          const uint64_t db = make_desc(sbase + ((seq + 2) & 3) * SLOT, 8192, 1024);
          token_wait(wg);
          wg_fence();
          wgmma_n256_rs(o, p[0], p[1], p[2], p[3], db, t != 0);
          wg_commit();
          wgmma_n256_rs(o, p[4], p[5], p[6], p[7], db + 128, 1);
          wgmma_n256_rs(o, p[8], p[9], p[10], p[11], db + 256, 1);
          wg_commit();
          wg_wait<1>();
          lds_v4(src + 3 * 512, p[12], p[13], p[14], p[15]);
          wg_fence();
          wgmma_n256_rs(o, p[12], p[13], p[14], p[15], db + 384, 1);
          wg_commit();
          token_pass(wg);
          if (!last) {
            if (lane == 0) {
              mbar_expect_tx(pfull + pstage * 8, PMSG_W);
              mbar_arrive_remote(pempty_r + pstage * 8);
            }
            if (++pstage == PST) { pstage = 0; pphase ^= 1; }
          }
          seq++;
          if (!last) {
            mbar_wait(pfull + pstage * 8, pphase);
            asm volatile("ld.shared.v2.b32 {%0, %1}, [%2];" : "=r"(ua0), "=r"(ua1) : "r"(mstat + pstage * PMSG_W) : "memory");
          }
          wg_wait<0>();
          fence_regs(o);
          if (release_slot(bars + (BAR_VREL + ((seq + 1) & 3)) * 8, lane) == 11) issue_ring(m, seq - 1 + NS_O, sbase, b0, h, 1);
          __syncwarp();
          if (!last) mbar_wait(bars + (BAR_VF + ((seq + 2) & 3)) * 8, (seq >> 2) & 1);
        };
#pragma unroll 1
        for (int t = 0; t < NKT - 1; t++) pv_step(t, false);
        pv_step(NKT - 1, true);
        uint32_t ui0, ui1;
        asm volatile("ld.shared.v2.b32 {%0, %1}, [%2];" : "=r"(ui0), "=r"(ui1) : "r"(mstat + pstage * PMSG_W + 8) : "memory");
        const float i0 = __uint_as_float(ui0), i1 = __uint_as_float(ui1);
#pragma unroll
        for (int j = 31; j >= 0; j--) {
          of[2 * j + 1] = pack_bf16_v(o[4 * j + 2] * i1, o[4 * j + 3] * i1);
          of[2 * j] = pack_bf16_v(o[4 * j] * i0, o[4 * j + 1] * i0);
        }
        __syncwarp();
        if (lane == 0) {
          mbar_expect_tx(pfull + pstage * 8, PMSG_W);
          mbar_arrive_remote(pempty_r + pstage * 8);
        }
        if (++pstage == PST) { pstage = 0; pphase ^= 1; }
      }
      if (it == 0) {
        mbar_wait(bars + BAR_XFREE * 8, 1);
#pragma unroll
        for (int j = 0; j < 16; j++) st_async_v4(xbuf_r + j * 512, of[4 * j], of[4 * j + 1], of[4 * j + 2], of[4 * j + 3], xf_r);
      } else {
        oproj(of);
      }
    }
  }
  __threadfence();
  __syncwarp();
  if (lane == 0) atomicAdd(g_cnt + rank, 1u);
  {
    uint4 va[NH];
    const int u = rank * 768 + cl * 12 + warp;
    wait_all(tid, 0);
    if (u < 4 * SLICES_PER_B) {
      slice_load(u, lane, va);
      slice_store(u, lane, va, out);
    }
    wait_all(tid, 1);
    if (u < 4 * SLICES_PER_B) {
      slice_load(4 * SLICES_PER_B + u, lane, va);
      slice_store(4 * SLICES_PER_B + u, lane, va, out);
    }
    __syncwarp();
    if (lane == 0) {
      if (atomicAdd(g_done, 1u) == 128 * 12 - 1) { g_cnt[0] = 0; g_cnt[1] = 0; g_done[0] = 0; }
    }
  }
}

typedef CUresult (*PFN_encodeTiled)(CUtensorMap*, CUtensorMapDataType, cuuint32_t, void*, const cuuint64_t*, const cuuint64_t*,
                                    const cuuint32_t*, const cuuint32_t*, CUtensorMapInterleave, CUtensorMapSwizzle,
                                    CUtensorMapL2promotion, CUtensorMapFloatOOBfill);

void encode(PFN_encodeTiled fn, CUtensorMap* m, int rank, const void* ptr, const cuuint64_t* dims, const cuuint64_t* strides,
            const cuuint32_t* box) {
  cuuint32_t es[3] = {1, 1, 1};
  fn(m, CU_TENSOR_MAP_DATA_TYPE_BFLOAT16, (cuuint32_t)rank, const_cast<void*>(ptr), dims, strides, box, es,
     CU_TENSOR_MAP_INTERLEAVE_NONE, CU_TENSOR_MAP_SWIZZLE_128B, CU_TENSOR_MAP_L2_PROMOTION_L2_256B,
     CU_TENSOR_MAP_FLOAT_OOB_FILL_NONE);
}

}

extern "C" void kernel_launch(void* const* d_in, const int* in_sizes, int n_in, void* d_out, int out_size) {
  const void* x = d_in[0];
  const void* kc = d_in[1];
  const void* vc = d_in[2];
  const void* wq = d_in[3];
  const void* wo = d_in[4];

  static PFN_encodeTiled fn = nullptr;
  if (!fn) {
    void* p = nullptr;
    cudaDriverEntryPointQueryResult qr;
    cudaGetDriverEntryPoint("cuTensorMapEncodeTiled", &p, cudaEnableDefault, &qr);
    fn = (PFN_encodeTiled)p;
    cudaFuncSetAttribute(mha_kernel, cudaFuncAttributeMaxDynamicSharedMemorySize, SMEM_BYTES);
  }
  CUtensorMap tm_x, tm_wq, tm_k, tm_v, tm_wo;
  {
    cuuint64_t dims[2] = {DM, (cuuint64_t)NB * SQ};
    cuuint64_t str[1] = {DM * 2};
    cuuint32_t box[2] = {64, SQ};
    encode(fn, &tm_x, 2, x, dims, str, box);
  }
  {
    cuuint64_t dims[3] = {64, DM, (cuuint64_t)NH * DH / 64};
    cuuint64_t str[2] = {(cuuint64_t)NH * DH * 2, 128};
    cuuint32_t box[3] = {64, 64, 4};
    encode(fn, &tm_wq, 3, wq, dims, str, box);
  }
  {
    cuuint64_t dims[3] = {64, (cuuint64_t)NB * NH * SK, 4};
    cuuint64_t str[2] = {DH * 2, 128};
    cuuint32_t box[3] = {64, 64, 4};
    encode(fn, &tm_k, 3, kc, dims, str, box);
    encode(fn, &tm_v, 3, vc, dims, str, box);
  }
  {
    cuuint64_t dims[2] = {DM, (cuuint64_t)NH * DH};
    cuuint64_t str[1] = {DM * 2};
    cuuint32_t box[2] = {64, DH};
    encode(fn, &tm_wo, 2, wo, dims, str, box);
  }
  mha_kernel<<<128, 384, SMEM_BYTES>>>(tm_x, tm_wq, tm_k, tm_v, tm_wo, (const __nv_bfloat16*)kc, (const __nv_bfloat16*)vc,
                                       (const __nv_bfloat16*)x, (const __nv_bfloat16*)wq, (__nv_bfloat16*)d_out);
}
```
